```python
import torch

def _softmax(x, axis=-1):
    return torch.softmax(x, dim=axis)

def _gelu(x):
    return torch.nn.functional.gelu(x, approximate='tanh')

def _silu(x):
    return torch.nn.functional.silu(x)

def _sigmoid(x):
    return torch.sigmoid(x)

def _layernorm(x, axis=-1, eps=1e-05):
    m = x.mean(dim=axis, keepdim=True)
    v = x.var(dim=axis, keepdim=True, unbiased=False)
    return (x - m) / torch.sqrt(v + eps)

def _scatter_add(tgt, idx, src, axis=0):
    return tgt.clone().index_add_(axis, idx, src)

def _segment_sum(src, seg, n):
    out = torch.zeros((n,) + src.shape[1:], dtype=src.dtype)
    return out.index_add_(0, seg, src)

def _pad(x, pw):
    flat = tuple((v for pair in reversed(pw) for v in pair))
    return torch.nn.functional.pad(x, flat)
kernel_name = 'concat_heads__softmax_full_mha__memory_aug_recurrent_mem_tr__prompt'

def setup_inputs():

    _w = lambda a: (lambda t: t.to(torch.bfloat16) if t.is_floating_point() else t)(torch.as_tensor(a))

    def _A_setup():
        B, S, D = (1, 2048, 1024)
        return {'x': _w((lambda *s: torch.randn(*s, dtype=torch.bfloat16) * 0.2)(B, S, D)), 'wqkv': _w((lambda *s: torch.randn(*s, dtype=torch.bfloat16) * 0.2)(D, 3 * D)), 'wo': _w((lambda *s: torch.randn(*s, dtype=torch.bfloat16) * 0.05)(D, D))}
    _A_in = _A_setup()

    def _B_setup():
        B, S, Dm = (1, 2048, 1024)
        H, Dh = (32, 128)
        M, seg = (8, 32)
        seg = min(seg, S)
        S = S // seg * seg
        return {'x': _w((lambda *s: torch.randn(*s, dtype=torch.bfloat16) * 0.05)(B, S, Dm)), 'mem0': _w((lambda *s: torch.randn(*s, dtype=torch.bfloat16) * 1.6)(B, M, Dm)), 'Wq': _w((lambda *s: torch.randn(*s, dtype=torch.bfloat16) * 0.8)(Dm, H, Dh) * Dm ** (-0.5)), 'Wk': _w((lambda *s: torch.randn(*s, dtype=torch.bfloat16) * 0.8)(Dm, H, Dh) * Dm ** (-0.5)), 'Wv': _w((lambda *s: torch.randn(*s, dtype=torch.bfloat16) * 1.6)(Dm, H, Dh) * Dm ** (-0.5)), 'Wo': _w((lambda *s: torch.randn(*s, dtype=torch.bfloat16) * 1.6)(H, Dh, Dm) * (H * Dh) ** (-0.5)), 'seg_len': seg}
    _B_in = _B_setup()
    return {'A_x': _A_in['x'], 'A_wqkv': _A_in['wqkv'], 'A_wo': _A_in['wo'], 'B_x': _B_in['x'], 'B_mem0': _B_in['mem0'], 'B_Wq': _B_in['Wq'], 'B_Wk': _B_in['Wk'], 'B_Wv': _B_in['Wv'], 'B_Wo': _B_in['Wo'], 'B_seg_len': _B_in['seg_len']}

def reference(A_x, A_wqkv, A_wo, B_x, B_mem0, B_Wq, B_Wk, B_Wv, B_Wo, B_seg_len):

    def _A_ref(x, wqkv, wo):
        B, S, D = x.shape
        H = 32
        Dh = D // H
        qkv = (lambda x, *d: x.permute(*d))((x @ wqkv).reshape(B, S, 3, H, Dh), 2, 0, 3, 1, 4)
        q, k, v = (qkv[0], qkv[1], qkv[2])
        scale = Dh ** (-0.5)
        scores = torch.einsum('bhqd,bhkd->bhqk', q, k) * scale
        p = _softmax(scores, axis=-1)
        o = torch.einsum('bhqk,bhkd->bhqd', p, v)
        return (lambda x, *d: x.permute(*d))(o, 0, 2, 1, 3).reshape(B, S, D) @ wo

    def _B_ref(x, mem0, Wq, Wk, Wv, Wo, seg_len):
        B, S, Dm = x.shape
        H, Dh = (Wq.shape[1], Wq.shape[2])
        M = mem0.shape[1]
        scale = Dh ** (-0.5)
        n_seg = S // seg_len
        L = M + seg_len
        idx = torch.arange(L)
        mask = (idx[:, None] < M) | (idx[:, None] >= idx[None, :])
        mem = mem0
        outs = []
        for s in range(n_seg):
            xs = x[:, s * seg_len:(s + 1) * seg_len, :].clone()
            h = torch.concatenate([mem, xs], axis=1)
            q = torch.einsum('btd,dhe->bhte', h, Wq)
            k = torch.einsum('btd,dhe->bhte', h, Wk)
            v = torch.einsum('btd,dhe->bhte', h, Wv)
            scores = torch.einsum('bhqe,bhke->bhqk', q, k) * scale
            scores = torch.where(mask[None, None], scores, -1000000000.0)
            p = _softmax(scores, axis=-1)
            o = torch.einsum('bhqk,bhke->bhqe', p, v)
            o = torch.einsum('bhte,hed->btd', o, Wo)
            mem = o[:, :M, :].clone()
            outs.append(o[:, M:, :])
        return torch.concatenate(outs, axis=1)
    a = _A_ref(A_x, A_wqkv, A_wo)
    b = _B_ref(B_x, B_mem0, B_Wq, B_Wk, B_Wv, B_Wo, B_seg_len)
    return torch.concatenate([a, b], axis=-1)
```

```cpp
#include <cuda_runtime.h>
#include <cuda_bf16.h>
#include <cuda.h>
#include <stdint.h>

typedef __nv_bfloat16 bf16;

#define SPIN_LIMIT (1 << 22)
#define KT_BEGIN(id)
#define KT_END(id)

__device__ __forceinline__ uint32_t s2u(const void* p) { return (uint32_t)__cvta_generic_to_shared(p); }
__device__ __forceinline__ void mbar_init(uint32_t b, uint32_t c) { asm volatile("mbarrier.init.shared::cta.b64 [%0], %1;" ::"r"(b), "r"(c) : "memory"); }
__device__ __forceinline__ void mbar_expect_tx(uint32_t b, uint32_t bytes) { asm volatile("mbarrier.arrive.expect_tx.shared::cta.b64 _, [%0], %1;" ::"r"(b), "r"(bytes) : "memory"); }
__device__ __forceinline__ void mbar_arrive(uint32_t b) { asm volatile("mbarrier.arrive.shared::cta.b64 _, [%0];" ::"r"(b) : "memory"); }
__device__ __forceinline__ uint32_t mbar_try(uint32_t b, uint32_t ph) {
  uint32_t ok;
  asm volatile("{.reg .pred p; mbarrier.test_wait.parity.shared::cta.b64 p, [%1], %2; selp.u32 %0,1,0,p;}" : "=r"(ok) : "r"(b), "r"(ph) : "memory");
  return ok;
}
__device__ __forceinline__ void mbar_wait(uint32_t b, uint32_t ph) {
  asm volatile(
      "{.reg .pred p; .reg .u32 n;\n"
      "mbarrier.try_wait.parity.shared::cta.b64 p, [%0], %1;\n"
      "@p bra.uni DONE;\n"
      "mov.u32 n, 0;\n"
      "LOOP:\n"
      "mbarrier.try_wait.parity.shared::cta.b64 p, [%0], %1;\n"
      "@p bra.uni DONE;\n"
      "add.u32 n, n, 1;\n"
      "setp.lt.u32 p, n, 4194304;\n"
      "@p bra.uni LOOP;\n"
      "trap;\n"
      "DONE:}\n" ::"r"(b), "r"(ph) : "memory");
}
__device__ __forceinline__ void mbar_wait_tok(uint32_t b, uint32_t ph, uint32_t tok) {
  asm volatile(
      "{.reg .pred p; .reg .u32 n;\n"
      "setp.ne.u32 p, %2, 0;\n"
      "@p bra.uni DONE;\n"
      "mov.u32 n, 0;\n"
      "LOOP:\n"
      "mbarrier.try_wait.parity.shared::cta.b64 p, [%0], %1;\n"
      "@p bra.uni DONE;\n"
      "add.u32 n, n, 1;\n"
      "setp.lt.u32 p, n, 4194304;\n"
      "@p bra.uni LOOP;\n"
      "trap;\n"
      "DONE:}\n" ::"r"(b), "r"(ph), "r"(tok) : "memory");
}
__device__ __forceinline__ void fence_mbar_init() { asm volatile("fence.mbarrier_init.release.cluster;" ::: "memory"); }
__device__ __forceinline__ void fence_proxy_async() { asm volatile("fence.proxy.async.shared::cta;" ::: "memory"); }
__device__ __forceinline__ void named_sync(int id, int n) { asm volatile("bar.sync %0, %1;" ::"r"(id), "r"(n) : "memory"); }
__device__ __forceinline__ void named_arrive(int id, int n) { asm volatile("bar.arrive %0, %1;" ::"r"(id), "r"(n) : "memory"); }
__device__ __forceinline__ void cluster_sync_all() { asm volatile("barrier.cluster.arrive.aligned; barrier.cluster.wait.aligned;" ::: "memory"); }
__device__ __forceinline__ uint32_t mapa(uint32_t a, uint32_t r) {
  uint32_t o;
  asm volatile("mapa.shared::cluster.u32 %0, %1, %2;" : "=r"(o) : "r"(a), "r"(r));
  return o;
}
__device__ __forceinline__ void tma_load_2d(uint32_t dst, const CUtensorMap* tm, int c0, int c1, uint32_t mb) {
  asm volatile("cp.async.bulk.tensor.2d.shared::cluster.global.mbarrier::complete_tx::bytes [%0], [%1, {%3, %4}], [%2];"
               ::"r"(dst), "l"(tm), "r"(mb), "r"(c0), "r"(c1) : "memory");
}
__device__ __forceinline__ void tma_load_2d_mc(uint32_t dst, const CUtensorMap* tm, int c0, int c1, uint32_t mb, uint16_t mask) {
  asm volatile("cp.async.bulk.tensor.2d.shared::cluster.global.mbarrier::complete_tx::bytes.multicast::cluster [%0], [%1, {%3, %4}], [%2], %5;"
               ::"r"(dst), "l"(tm), "r"(mb), "r"(c0), "r"(c1), "h"(mask) : "memory");
}
__device__ __forceinline__ void tma_store_2d(const CUtensorMap* tm, uint32_t src, int c0, int c1) {
  asm volatile("cp.async.bulk.tensor.2d.global.shared::cta.bulk_group [%0, {%2, %3}], [%1];" ::"l"(tm), "r"(src), "r"(c0), "r"(c1) : "memory");
}
__device__ __forceinline__ void bulk_commit() { asm volatile("cp.async.bulk.commit_group;" ::: "memory"); }
__device__ __forceinline__ void bulk_wait0() { asm volatile("cp.async.bulk.wait_group 0;" ::: "memory"); }
__device__ __forceinline__ void prefetch_tmap(const CUtensorMap* tm) { asm volatile("prefetch.tensormap [%0];" ::"l"(tm) : "memory"); }

__device__ __forceinline__ void wg_fence() { asm volatile("wgmma.fence.sync.aligned;" ::: "memory"); }
__device__ __forceinline__ void wg_commit() { asm volatile("wgmma.commit_group.sync.aligned;" ::: "memory"); }
template <int N> __device__ __forceinline__ void wg_wait() { asm volatile("wgmma.wait_group.sync.aligned %0;" ::"n"(N) : "memory"); }
template <int N> __device__ __forceinline__ void reg_fence(float* d) {
#pragma unroll
  for (int i = 0; i < N; i++) asm volatile("" : "+f"(d[i])::"memory");
}
__device__ __forceinline__ uint64_t mkdesc(uint32_t addr, uint32_t lbo, uint32_t sbo, uint32_t swz) {
  return (uint64_t)((addr & 0x3FFFF) >> 4) | ((uint64_t)(lbo >> 4) << 16) | ((uint64_t)(sbo >> 4) << 32) | ((uint64_t)swz << 62);
}
__device__ __forceinline__ uint64_t mkd(uint32_t lo, uint32_t hi) { return ((uint64_t)hi << 32) | lo; }
__device__ __forceinline__ uint32_t pack_bf16(float lo, float hi) {
  uint32_t r;
  asm("cvt.rn.bf16x2.f32 %0, %1, %2;" : "=r"(r) : "f"(hi), "f"(lo));
  return r;
}
__device__ __forceinline__ float ex2(float x) {
  float y;
  asm("ex2.approx.ftz.f32 %0, %1;" : "=f"(y) : "f"(x));
  return y;
}
__device__ __forceinline__ float ex2v(float x) {
  float y;
  asm volatile("ex2.approx.ftz.f32 %0, %1;" : "=f"(y) : "f"(x));
  return y;
}
__device__ __forceinline__ void mbar_arrive_elect(uint32_t a) {
  asm volatile("{.reg .pred p; elect.sync _|p, 0xffffffff; @p mbarrier.arrive.shared::cluster.b64 _, [%0];}" ::"r"(a) : "memory");
}
__device__ __forceinline__ void stmatrix_x4(uint32_t a, uint32_t r0, uint32_t r1, uint32_t r2, uint32_t r3) {
  asm volatile("stmatrix.sync.aligned.m8n8.x4.shared.b16 [%0], {%1,%2,%3,%4};" ::"r"(a), "r"(r0), "r"(r1), "r"(r2), "r"(r3) : "memory");
}
__device__ __forceinline__ void stmatrix_x4_t(uint32_t a, uint32_t r0, uint32_t r1, uint32_t r2, uint32_t r3) {
  asm volatile("stmatrix.sync.aligned.m8n8.x4.trans.shared.b16 [%0], {%1,%2,%3,%4};" ::"r"(a), "r"(r0), "r"(r1), "r"(r2), "r"(r3) : "memory");
}
__device__ __forceinline__ void stmatrix_x2(uint32_t a, uint32_t r0, uint32_t r1) {
  asm volatile("stmatrix.sync.aligned.m8n8.x2.shared.b16 [%0], {%1,%2};" ::"r"(a), "r"(r0), "r"(r1) : "memory");
}
__device__ __forceinline__ void ldmatrix_x4(uint32_t a, uint32_t& r0, uint32_t& r1, uint32_t& r2, uint32_t& r3) {
  asm volatile("ldmatrix.sync.aligned.m8n8.x4.shared.b16 {%0,%1,%2,%3}, [%4];" : "=r"(r0), "=r"(r1), "=r"(r2), "=r"(r3) : "r"(a) : "memory");
}
__device__ __forceinline__ void ldmatrix_x4_t(uint32_t a, uint32_t& r0, uint32_t& r1, uint32_t& r2, uint32_t& r3) {
  asm volatile("ldmatrix.sync.aligned.m8n8.x4.trans.shared.b16 {%0,%1,%2,%3}, [%4];" : "=r"(r0), "=r"(r1), "=r"(r2), "=r"(r3) : "r"(a) : "memory");
}
__device__ __forceinline__ void ldmatrix_x2_t(uint32_t a, uint32_t& r0, uint32_t& r1) {
  asm volatile("ldmatrix.sync.aligned.m8n8.x2.trans.shared.b16 {%0,%1}, [%2];" : "=r"(r0), "=r"(r1) : "r"(a) : "memory");
}
__device__ __forceinline__ void ldmatrix_x1(uint32_t a, uint32_t& r0) {
  asm volatile("ldmatrix.sync.aligned.m8n8.x1.shared.b16 {%0}, [%1];" : "=r"(r0) : "r"(a) : "memory");
}
__device__ __forceinline__ void mma16816(float (&d)[4], uint32_t a0, uint32_t a1, uint32_t a2, uint32_t a3, uint32_t b0, uint32_t b1) {
  asm("mma.sync.aligned.m16n8k16.row.col.f32.bf16.bf16.f32 {%0,%1,%2,%3}, {%4,%5,%6,%7}, {%8,%9}, {%0,%1,%2,%3};"
               : "+f"(d[0]), "+f"(d[1]), "+f"(d[2]), "+f"(d[3]) : "r"(a0), "r"(a1), "r"(a2), "r"(a3), "r"(b0), "r"(b1));
}
__device__ __forceinline__ void mma16816v(float (&d)[4], uint32_t a0, uint32_t a1, uint32_t a2, uint32_t a3, uint32_t b0, uint32_t b1) {
  asm volatile("mma.sync.aligned.m16n8k16.row.col.f32.bf16.bf16.f32 {%0,%1,%2,%3}, {%4,%5,%6,%7}, {%8,%9}, {%0,%1,%2,%3};"
               : "+f"(d[0]), "+f"(d[1]), "+f"(d[2]), "+f"(d[3]) : "r"(a0), "r"(a1), "r"(a2), "r"(a3), "r"(b0), "r"(b1));
}
__device__ __forceinline__ void mma1688(float (&d)[4], uint32_t a0, uint32_t a1, uint32_t b0) {
  asm("mma.sync.aligned.m16n8k8.row.col.f32.bf16.bf16.f32 {%0,%1,%2,%3}, {%4,%5}, {%6}, {%0,%1,%2,%3};"
               : "+f"(d[0]), "+f"(d[1]), "+f"(d[2]), "+f"(d[3]) : "r"(a0), "r"(a1), "r"(b0));
}
__device__ __forceinline__ uint32_t movmatrix_t(uint32_t a) {
  uint32_t d;
  asm volatile("movmatrix.sync.aligned.m8n8.trans.b16 %0, %1;" : "=r"(d) : "r"(a));
  return d;
}

template <int TA, int TB>
__device__ __forceinline__ void wgmma_ss_n32_z(float* d, uint64_t da, uint64_t db) {
  asm volatile("{.reg .pred p; setp.ne.b32 p, 0, 0;\n"
    "wgmma.mma_async.sync.aligned.m64n32k16.f32.bf16.bf16 {%0,%1,%2,%3,%4,%5,%6,%7,%8,%9,%10,%11,%12,%13,%14,%15}, %16, %17, p, 1, 1, %18, %19;}\n"
    : "=f"(d[0]), "=f"(d[1]), "=f"(d[2]), "=f"(d[3]), "=f"(d[4]), "=f"(d[5]), "=f"(d[6]), "=f"(d[7]), "=f"(d[8]), "=f"(d[9]), "=f"(d[10]), "=f"(d[11]), "=f"(d[12]), "=f"(d[13]), "=f"(d[14]), "=f"(d[15])
    : "l"(da), "l"(db), "n"(TA), "n"(TB));
}
template <int TA, int TB>
__device__ __forceinline__ void wgmma_ss_n40_z(float* d, uint64_t da, uint64_t db) {
  asm volatile("{.reg .pred p; setp.ne.b32 p, 0, 0;\n"
    "wgmma.mma_async.sync.aligned.m64n40k16.f32.bf16.bf16 {%0,%1,%2,%3,%4,%5,%6,%7,%8,%9,%10,%11,%12,%13,%14,%15,%16,%17,%18,%19}, %20, %21, p, 1, 1, %22, %23;}\n"
    : "=f"(d[0]), "=f"(d[1]), "=f"(d[2]), "=f"(d[3]), "=f"(d[4]), "=f"(d[5]), "=f"(d[6]), "=f"(d[7]), "=f"(d[8]), "=f"(d[9]), "=f"(d[10]), "=f"(d[11]), "=f"(d[12]), "=f"(d[13]), "=f"(d[14]), "=f"(d[15]), "=f"(d[16]), "=f"(d[17]), "=f"(d[18]), "=f"(d[19])
    : "l"(da), "l"(db), "n"(TA), "n"(TB));
}
template <int TA, int TB>
__device__ __forceinline__ void wgmma_ss_n128_z(float* d, uint64_t da, uint64_t db) {
  asm volatile("{.reg .pred p; setp.ne.b32 p, 0, 0;\n"
    "wgmma.mma_async.sync.aligned.m64n128k16.f32.bf16.bf16 {%0,%1,%2,%3,%4,%5,%6,%7,%8,%9,%10,%11,%12,%13,%14,%15,%16,%17,%18,%19,%20,%21,%22,%23,%24,%25,%26,%27,%28,%29,%30,%31,%32,%33,%34,%35,%36,%37,%38,%39,%40,%41,%42,%43,%44,%45,%46,%47,%48,%49,%50,%51,%52,%53,%54,%55,%56,%57,%58,%59,%60,%61,%62,%63}, %64, %65, p, 1, 1, %66, %67;}\n"
    : "=f"(d[0]), "=f"(d[1]), "=f"(d[2]), "=f"(d[3]), "=f"(d[4]), "=f"(d[5]), "=f"(d[6]), "=f"(d[7]), "=f"(d[8]), "=f"(d[9]), "=f"(d[10]), "=f"(d[11]), "=f"(d[12]), "=f"(d[13]), "=f"(d[14]), "=f"(d[15]), "=f"(d[16]), "=f"(d[17]), "=f"(d[18]), "=f"(d[19]), "=f"(d[20]), "=f"(d[21]), "=f"(d[22]), "=f"(d[23]), "=f"(d[24]), "=f"(d[25]), "=f"(d[26]), "=f"(d[27]), "=f"(d[28]), "=f"(d[29]), "=f"(d[30]), "=f"(d[31]), "=f"(d[32]), "=f"(d[33]), "=f"(d[34]), "=f"(d[35]), "=f"(d[36]), "=f"(d[37]), "=f"(d[38]), "=f"(d[39]), "=f"(d[40]), "=f"(d[41]), "=f"(d[42]), "=f"(d[43]), "=f"(d[44]), "=f"(d[45]), "=f"(d[46]), "=f"(d[47]), "=f"(d[48]), "=f"(d[49]), "=f"(d[50]), "=f"(d[51]), "=f"(d[52]), "=f"(d[53]), "=f"(d[54]), "=f"(d[55]), "=f"(d[56]), "=f"(d[57]), "=f"(d[58]), "=f"(d[59]), "=f"(d[60]), "=f"(d[61]), "=f"(d[62]), "=f"(d[63])
    : "l"(da), "l"(db), "n"(TA), "n"(TB));
}
template <int TB>
__device__ __forceinline__ void wgmma_rs_n8(float* d, uint32_t a0, uint32_t a1, uint32_t a2, uint32_t a3, uint64_t db, int scale_d) {
  asm volatile("{.reg .pred p; setp.ne.b32 p, %9, 0;\n"
    "wgmma.mma_async.sync.aligned.m64n8k16.f32.bf16.bf16 {%0,%1,%2,%3}, {%4,%5,%6,%7}, %8, p, 1, 1, %10;}\n"
    : "+f"(d[0]), "+f"(d[1]), "+f"(d[2]), "+f"(d[3])
    : "r"(a0), "r"(a1), "r"(a2), "r"(a3), "l"(db), "r"(scale_d), "n"(TB));
}
template <int TA, int TB>
__device__ __forceinline__ void wgmma_ss_n32(float* d, uint64_t da, uint64_t db, int scale_d) {
  asm volatile("{.reg .pred p; setp.ne.b32 p, %18, 0;\n"
    "wgmma.mma_async.sync.aligned.m64n32k16.f32.bf16.bf16 {%0,%1,%2,%3,%4,%5,%6,%7,%8,%9,%10,%11,%12,%13,%14,%15}, %16, %17, p, 1, 1, %19, %20;}\n"
    : "+f"(d[0]), "+f"(d[1]), "+f"(d[2]), "+f"(d[3]), "+f"(d[4]), "+f"(d[5]), "+f"(d[6]), "+f"(d[7]), "+f"(d[8]), "+f"(d[9]), "+f"(d[10]), "+f"(d[11]), "+f"(d[12]), "+f"(d[13]), "+f"(d[14]), "+f"(d[15])
    : "l"(da), "l"(db), "r"(scale_d), "n"(TA), "n"(TB));
}
template <int TB>
__device__ __forceinline__ void wgmma_rs_n32(float* d, uint32_t a0, uint32_t a1, uint32_t a2, uint32_t a3, uint64_t db, int scale_d) {
  asm volatile("{.reg .pred p; setp.ne.b32 p, %21, 0;\n"
    "wgmma.mma_async.sync.aligned.m64n32k16.f32.bf16.bf16 {%0,%1,%2,%3,%4,%5,%6,%7,%8,%9,%10,%11,%12,%13,%14,%15}, {%16,%17,%18,%19}, %20, p, 1, 1, %22;}\n"
    : "+f"(d[0]), "+f"(d[1]), "+f"(d[2]), "+f"(d[3]), "+f"(d[4]), "+f"(d[5]), "+f"(d[6]), "+f"(d[7]), "+f"(d[8]), "+f"(d[9]), "+f"(d[10]), "+f"(d[11]), "+f"(d[12]), "+f"(d[13]), "+f"(d[14]), "+f"(d[15])
    : "r"(a0), "r"(a1), "r"(a2), "r"(a3), "l"(db), "r"(scale_d), "n"(TB));
}
template <int TA, int TB>
__device__ __forceinline__ void wgmma_ss_n40(float* d, uint64_t da, uint64_t db, int scale_d) {
  asm volatile("{.reg .pred p; setp.ne.b32 p, %22, 0;\n"
    "wgmma.mma_async.sync.aligned.m64n40k16.f32.bf16.bf16 {%0,%1,%2,%3,%4,%5,%6,%7,%8,%9,%10,%11,%12,%13,%14,%15,%16,%17,%18,%19}, %20, %21, p, 1, 1, %23, %24;}\n"
    : "+f"(d[0]), "+f"(d[1]), "+f"(d[2]), "+f"(d[3]), "+f"(d[4]), "+f"(d[5]), "+f"(d[6]), "+f"(d[7]), "+f"(d[8]), "+f"(d[9]), "+f"(d[10]), "+f"(d[11]), "+f"(d[12]), "+f"(d[13]), "+f"(d[14]), "+f"(d[15]), "+f"(d[16]), "+f"(d[17]), "+f"(d[18]), "+f"(d[19])
    : "l"(da), "l"(db), "r"(scale_d), "n"(TA), "n"(TB));
}
template <int TB>
__device__ __forceinline__ void wgmma_rs_n40(float* d, uint32_t a0, uint32_t a1, uint32_t a2, uint32_t a3, uint64_t db, int scale_d) {
  asm volatile("{.reg .pred p; setp.ne.b32 p, %25, 0;\n"
    "wgmma.mma_async.sync.aligned.m64n40k16.f32.bf16.bf16 {%0,%1,%2,%3,%4,%5,%6,%7,%8,%9,%10,%11,%12,%13,%14,%15,%16,%17,%18,%19}, {%20,%21,%22,%23}, %24, p, 1, 1, %26;}\n"
    : "+f"(d[0]), "+f"(d[1]), "+f"(d[2]), "+f"(d[3]), "+f"(d[4]), "+f"(d[5]), "+f"(d[6]), "+f"(d[7]), "+f"(d[8]), "+f"(d[9]), "+f"(d[10]), "+f"(d[11]), "+f"(d[12]), "+f"(d[13]), "+f"(d[14]), "+f"(d[15]), "+f"(d[16]), "+f"(d[17]), "+f"(d[18]), "+f"(d[19])
    : "r"(a0), "r"(a1), "r"(a2), "r"(a3), "l"(db), "r"(scale_d), "n"(TB));
}
template <int TA, int TB>
__device__ __forceinline__ void wgmma_ss_n128(float* d, uint64_t da, uint64_t db, int scale_d) {
  asm volatile("{.reg .pred p; setp.ne.b32 p, %66, 0;\n"
    "wgmma.mma_async.sync.aligned.m64n128k16.f32.bf16.bf16 {%0,%1,%2,%3,%4,%5,%6,%7,%8,%9,%10,%11,%12,%13,%14,%15,%16,%17,%18,%19,%20,%21,%22,%23,%24,%25,%26,%27,%28,%29,%30,%31,%32,%33,%34,%35,%36,%37,%38,%39,%40,%41,%42,%43,%44,%45,%46,%47,%48,%49,%50,%51,%52,%53,%54,%55,%56,%57,%58,%59,%60,%61,%62,%63}, %64, %65, p, 1, 1, %67, %68;}\n"
    : "+f"(d[0]), "+f"(d[1]), "+f"(d[2]), "+f"(d[3]), "+f"(d[4]), "+f"(d[5]), "+f"(d[6]), "+f"(d[7]), "+f"(d[8]), "+f"(d[9]), "+f"(d[10]), "+f"(d[11]), "+f"(d[12]), "+f"(d[13]), "+f"(d[14]), "+f"(d[15]), "+f"(d[16]), "+f"(d[17]), "+f"(d[18]), "+f"(d[19]), "+f"(d[20]), "+f"(d[21]), "+f"(d[22]), "+f"(d[23]), "+f"(d[24]), "+f"(d[25]), "+f"(d[26]), "+f"(d[27]), "+f"(d[28]), "+f"(d[29]), "+f"(d[30]), "+f"(d[31]), "+f"(d[32]), "+f"(d[33]), "+f"(d[34]), "+f"(d[35]), "+f"(d[36]), "+f"(d[37]), "+f"(d[38]), "+f"(d[39]), "+f"(d[40]), "+f"(d[41]), "+f"(d[42]), "+f"(d[43]), "+f"(d[44]), "+f"(d[45]), "+f"(d[46]), "+f"(d[47]), "+f"(d[48]), "+f"(d[49]), "+f"(d[50]), "+f"(d[51]), "+f"(d[52]), "+f"(d[53]), "+f"(d[54]), "+f"(d[55]), "+f"(d[56]), "+f"(d[57]), "+f"(d[58]), "+f"(d[59]), "+f"(d[60]), "+f"(d[61]), "+f"(d[62]), "+f"(d[63])
    : "l"(da), "l"(db), "r"(scale_d), "n"(TA), "n"(TB));
}
template <int TA, int TB>
__device__ __forceinline__ void wgmma_ss_n256(float* d, uint64_t da, uint64_t db, int scale_d) {
  asm volatile("{.reg .pred p; setp.ne.b32 p, %130, 0;\n"
    "wgmma.mma_async.sync.aligned.m64n256k16.f32.bf16.bf16 {%0,%1,%2,%3,%4,%5,%6,%7,%8,%9,%10,%11,%12,%13,%14,%15,%16,%17,%18,%19,%20,%21,%22,%23,%24,%25,%26,%27,%28,%29,%30,%31,%32,%33,%34,%35,%36,%37,%38,%39,%40,%41,%42,%43,%44,%45,%46,%47,%48,%49,%50,%51,%52,%53,%54,%55,%56,%57,%58,%59,%60,%61,%62,%63,%64,%65,%66,%67,%68,%69,%70,%71,%72,%73,%74,%75,%76,%77,%78,%79,%80,%81,%82,%83,%84,%85,%86,%87,%88,%89,%90,%91,%92,%93,%94,%95,%96,%97,%98,%99,%100,%101,%102,%103,%104,%105,%106,%107,%108,%109,%110,%111,%112,%113,%114,%115,%116,%117,%118,%119,%120,%121,%122,%123,%124,%125,%126,%127}, %128, %129, p, 1, 1, %131, %132;}\n"
    : "+f"(d[0]), "+f"(d[1]), "+f"(d[2]), "+f"(d[3]), "+f"(d[4]), "+f"(d[5]), "+f"(d[6]), "+f"(d[7]), "+f"(d[8]), "+f"(d[9]), "+f"(d[10]), "+f"(d[11]), "+f"(d[12]), "+f"(d[13]), "+f"(d[14]), "+f"(d[15]), "+f"(d[16]), "+f"(d[17]), "+f"(d[18]), "+f"(d[19]), "+f"(d[20]), "+f"(d[21]), "+f"(d[22]), "+f"(d[23]), "+f"(d[24]), "+f"(d[25]), "+f"(d[26]), "+f"(d[27]), "+f"(d[28]), "+f"(d[29]), "+f"(d[30]), "+f"(d[31]), "+f"(d[32]), "+f"(d[33]), "+f"(d[34]), "+f"(d[35]), "+f"(d[36]), "+f"(d[37]), "+f"(d[38]), "+f"(d[39]), "+f"(d[40]), "+f"(d[41]), "+f"(d[42]), "+f"(d[43]), "+f"(d[44]), "+f"(d[45]), "+f"(d[46]), "+f"(d[47]), "+f"(d[48]), "+f"(d[49]), "+f"(d[50]), "+f"(d[51]), "+f"(d[52]), "+f"(d[53]), "+f"(d[54]), "+f"(d[55]), "+f"(d[56]), "+f"(d[57]), "+f"(d[58]), "+f"(d[59]), "+f"(d[60]), "+f"(d[61]), "+f"(d[62]), "+f"(d[63]), "+f"(d[64]), "+f"(d[65]), "+f"(d[66]), "+f"(d[67]), "+f"(d[68]), "+f"(d[69]), "+f"(d[70]), "+f"(d[71]), "+f"(d[72]), "+f"(d[73]), "+f"(d[74]), "+f"(d[75]), "+f"(d[76]), "+f"(d[77]), "+f"(d[78]), "+f"(d[79]), "+f"(d[80]), "+f"(d[81]), "+f"(d[82]), "+f"(d[83]), "+f"(d[84]), "+f"(d[85]), "+f"(d[86]), "+f"(d[87]), "+f"(d[88]), "+f"(d[89]), "+f"(d[90]), "+f"(d[91]), "+f"(d[92]), "+f"(d[93]), "+f"(d[94]), "+f"(d[95]), "+f"(d[96]), "+f"(d[97]), "+f"(d[98]), "+f"(d[99]), "+f"(d[100]), "+f"(d[101]), "+f"(d[102]), "+f"(d[103]), "+f"(d[104]), "+f"(d[105]), "+f"(d[106]), "+f"(d[107]), "+f"(d[108]), "+f"(d[109]), "+f"(d[110]), "+f"(d[111]), "+f"(d[112]), "+f"(d[113]), "+f"(d[114]), "+f"(d[115]), "+f"(d[116]), "+f"(d[117]), "+f"(d[118]), "+f"(d[119]), "+f"(d[120]), "+f"(d[121]), "+f"(d[122]), "+f"(d[123]), "+f"(d[124]), "+f"(d[125]), "+f"(d[126]), "+f"(d[127])
    : "l"(da), "l"(db), "r"(scale_d), "n"(TA), "n"(TB));
}

__device__ unsigned g_pass[16];
__device__ unsigned g_prog[16];

template <int BN> struct GemmAcc;
template <> struct GemmAcc<128> { static __device__ __forceinline__ void mma(float* d, uint64_t a, uint64_t b, int s) { wgmma_ss_n128<0, 1>(d, a, b, s); } };
template <> struct GemmAcc<256> { static __device__ __forceinline__ void mma(float* d, uint64_t a, uint64_t b, int s) { wgmma_ss_n256<0, 1>(d, a, b, s); } };

template <int BN, int STAGES, int MINB, int SPLIT>
__global__ void __launch_bounds__(288, MINB)
gemm_kernel(const __grid_constant__ CUtensorMap tmA, const __grid_constant__ CUtensorMap tmB,
            const __grid_constant__ CUtensorMap tmC, int K, int tiles_n, int coff, int tm0, int gated, int kid) {
  extern __shared__ __align__(1024) uint8_t smem_raw[];
  constexpr int A_BYTES = 128 * 128, B_BYTES = BN * 128, STAGE = A_BYTES + B_BYTES;
  const uint32_t sb = s2u(smem_raw);
  const uint32_t xch = sb + STAGES * STAGE;
  const uint32_t bars = xch + (SPLIT == 2 ? BN * 256 : 0);
  const int tid = threadIdx.x, warp = __shfl_sync(~0u, tid >> 5, 0), lane = tid & 31;
  const int tile = blockIdx.x / SPLIT, half = blockIdx.x % SPLIT;
  const int tn = tile % tiles_n, tm = tile / tiles_n + tm0;
  KT_BEGIN(kid);
  if (kid == 5) KT_END(4);
  const int m0 = tm * 128, n0 = gated == 2 ? (tn >> 1) * 1024 + 768 + (tn & 1) * 128 : tn * BN;
  const int nk = (K >> 6) / SPLIT, k0 = half * nk;
  if (tid == 0) {
    for (int s = 0; s < STAGES; s++) { mbar_init(bars + 8 * s, 1); mbar_init(bars + 8 * (STAGES + s), 8); }
    if (SPLIT == 2) { mbar_init(bars + 16 * STAGES, 1); mbar_expect_tx(bars + 16 * STAGES, BN * 256); }
    fence_mbar_init();
  }
  __syncthreads();
  if (SPLIT == 2) asm volatile("barrier.cluster.arrive.aligned;" ::: "memory");
  if (warp == 8) {
    if (lane == 0) {
      prefetch_tmap(&tmA); prefetch_tmap(&tmB);
      if (gated == 1) {
        unsigned v;
        for (int n = 0;; n++) {
          asm volatile("ld.acquire.gpu.global.u32 %0, [%1];" : "=r"(v) : "l"(&g_prog[tm]) : "memory");
          if (v == 128u) break;
          if (n > SPIN_LIMIT) __trap();
          __nanosleep(200);
        }
        if (atomicAdd(&g_pass[tm], 1u) == (unsigned)(tiles_n * SPLIT) - 1) { g_pass[tm] = 0; g_prog[tm] = 0; }
        asm volatile("fence.proxy.async.global;" ::: "memory");
      }
      int st = 0; uint32_t ph = 1;
      for (int k = 0; k < nk; k++) {
        mbar_wait(bars + 8 * (STAGES + st), ph);
        const uint32_t fb = bars + 8 * st, dst = sb + st * STAGE;
        mbar_expect_tx(fb, STAGE);
        tma_load_2d(dst, &tmA, (k0 + k) * 64, m0, fb);
#pragma unroll
        for (int j = 0; j < BN / 64; j++) tma_load_2d(dst + A_BYTES + j * 8192, &tmB, n0 + j * 64, (k0 + k) * 64, fb);
        if (++st == STAGES) { st = 0; ph ^= 1; }
      }
    }
    if (SPLIT == 2) {
      __syncwarp();
      asm volatile("barrier.cluster.wait.aligned;" ::: "memory");
      cluster_sync_all();
    }
  } else {
    const int wg = warp >> 2;
    float acc[BN / 2];
    const uint32_t ad0 = (((sb + wg * 8192) & 0x3FFFF) >> 4) | (1u << 16), bd0 = (((sb + A_BYTES) & 0x3FFFF) >> 4) | (512u << 16);
    int st = 0; uint32_t ph = 0;
    for (int k = 0; k < nk; k++) {
      mbar_wait(bars + 8 * st, ph);
      const uint32_t a0 = ad0 + st * (STAGE >> 4), b0 = bd0 + st * (STAGE >> 4);
      wg_fence();
#pragma unroll
      for (int kk = 0; kk < 4; kk++) GemmAcc<BN>::mma(acc, mkd(a0 + kk * 2, 0x40000040u), mkd(b0 + kk * 128, 0x40000040u), (k | kk) != 0);
      wg_commit();
      if (k > 0) {
        wg_wait<1>();
        int ps = st == 0 ? STAGES - 1 : st - 1;
        mbar_arrive_elect(bars + 8 * (STAGES + ps));
      }
      if (++st == STAGES) { st = 0; ph ^= 1; }
    }
    wg_wait<0>();
    reg_fence<BN / 2>(acc);
    named_sync(1, 256);
    if (SPLIT == 2) {
      asm volatile("barrier.cluster.wait.aligned;" ::: "memory");
      if (wg != half) {
        const uint32_t dst = mapa(xch + (tid & 127) * 16, half ^ 1), mb = mapa(bars + 16 * STAGES, half ^ 1);
#pragma unroll
        for (int j = 0; j < BN / 8; j++)
          asm volatile("st.async.weak.shared::cluster.mbarrier::complete_tx::bytes.v4.f32 [%0], {%1,%2,%3,%4}, [%5];" ::"r"(dst + j * 2048),
                       "f"(acc[4 * j]), "f"(acc[4 * j + 1]), "f"(acc[4 * j + 2]), "f"(acc[4 * j + 3]), "r"(mb) : "memory");
        cluster_sync_all();
        return;
      }
      mbar_wait(bars + 16 * STAGES, 0);
#pragma unroll
      for (int j = 0; j < BN / 8; j++) {
        float4 v;
        asm volatile("ld.shared.v4.f32 {%0,%1,%2,%3}, [%4];" : "=f"(v.x), "=f"(v.y), "=f"(v.z), "=f"(v.w) : "r"(xch + (tid & 127) * 16 + j * 2048) : "memory");
        acc[4 * j] += v.x; acc[4 * j + 1] += v.y; acc[4 * j + 2] += v.z; acc[4 * j + 3] += v.w;
      }
      asm volatile("barrier.cluster.arrive.aligned;" ::: "memory");
    }
    const uint32_t cb = sb + wg * (BN * 128);
    const int row = (warp & 3) * 16 + (lane & 7) + ((lane >> 3) & 1) * 8;
#pragma unroll
    for (int j = 0; j < BN / 16; j++) {
      uint32_t r0 = pack_bf16(acc[8 * j + 0], acc[8 * j + 1]), r1 = pack_bf16(acc[8 * j + 2], acc[8 * j + 3]);
      uint32_t r2 = pack_bf16(acc[8 * j + 4], acc[8 * j + 5]), r3 = pack_bf16(acc[8 * j + 6], acc[8 * j + 7]);
      const int chunk = (j & 3) * 2 + (lane >> 4);
      stmatrix_x4(cb + (j >> 2) * 8192 + row * 128 + ((chunk ^ (row & 7)) << 4), r0, r1, r2, r3);
    }
    fence_proxy_async();
    named_sync(2 + wg, 128);
    if ((tid & 127) == 0) {
#pragma unroll
      for (int j = 0; j < BN / 64; j++) tma_store_2d(&tmC, cb + j * 8192, coff + n0 + j * 64, m0 + wg * 64);
      bulk_commit();
      bulk_wait0();
    }
    if (SPLIT == 2) { __syncwarp(); asm volatile("barrier.cluster.wait.aligned;" ::: "memory"); }
    KT_END(kid);
    if (kid == 5) KT_BEGIN(4);
  }
}

__device__ __forceinline__ int qkv_col(int j) { return j + j / 3; }
constexpr int GP_SMEM = 4 * 49152 + 32768 + 128;
__global__ void __launch_bounds__(288, 1)
gemm_persist_kernel(const __grid_constant__ CUtensorMap tmA, const __grid_constant__ CUtensorMap tmB,
                    const __grid_constant__ CUtensorMap tmC, int K, int tiles_n, int ntiles, int kid) {
  extern __shared__ __align__(1024) uint8_t smem_raw[];
  constexpr int STAGES = 4, A_BYTES = 16384, STAGE = 49152;
  const uint32_t sb = s2u(smem_raw);
  const uint32_t bars = sb + STAGES * STAGE + 32768;
  const int tid = threadIdx.x, warp = __shfl_sync(~0u, tid >> 5, 0), lane = tid & 31;
  const int nk = K >> 6;
  KT_BEGIN(kid);
  if (tid == 0) {
    for (int s = 0; s < STAGES; s++) { mbar_init(bars + 8 * s, 1); mbar_init(bars + 8 * (STAGES + s), 8); }
    fence_mbar_init();
  }
  __syncthreads();
  if (warp == 8) {
    int st = 0; uint32_t ph = 1;
    for (int tile = blockIdx.x; tile < ntiles; tile += gridDim.x) {
      const int m0 = (tile / tiles_n) * 128, n0 = qkv_col(tile % tiles_n) * 256;
      for (int k = 0; k < nk; k++) {
        mbar_wait(bars + 8 * (STAGES + st), ph);
        const uint32_t fb = bars + 8 * st, dst = sb + st * STAGE;
        if (lane == 0) {
          mbar_expect_tx(fb, STAGE);
          tma_load_2d(dst, &tmA, k * 64, m0, fb);
#pragma unroll
          for (int j = 0; j < 4; j++) tma_load_2d(dst + A_BYTES + j * 8192, &tmB, n0 + j * 64, k * 64, fb);
        }
        __syncwarp();
        if (++st == STAGES) { st = 0; ph ^= 1; }
      }
    }
  } else {
    const int wg = warp >> 2;
    const uint32_t ad0 = (((sb + wg * 8192) & 0x3FFFF) >> 4) | (1u << 16), bd0 = (((sb + A_BYTES) & 0x3FFFF) >> 4) | (512u << 16);
    const uint32_t cb = sb + STAGES * STAGE + wg * 16384;
    const int row = (warp & 3) * 16 + (lane & 7) + ((lane >> 3) & 1) * 8;
    int st = 0; uint32_t ph = 0;
    for (int tile = blockIdx.x; tile < ntiles; tile += gridDim.x) {
      const int m0 = (tile / tiles_n) * 128, n0 = qkv_col(tile % tiles_n) * 256;
      float acc[128];
      for (int k = 0; k < nk; k++) {
        mbar_wait(bars + 8 * st, ph);
        const uint32_t a0 = ad0 + st * (STAGE >> 4), b0 = bd0 + st * (STAGE >> 4);
        wg_fence();
#pragma unroll
        for (int kk = 0; kk < 4; kk++) wgmma_ss_n256<0, 1>(acc, mkd(a0 + kk * 2, 0x40000040u), mkd(b0 + kk * 128, 0x40000040u), (k | kk) != 0);
        wg_commit();
        if (k > 0) {
          wg_wait<1>();
          mbar_arrive_elect(bars + 8 * (STAGES + (st == 0 ? STAGES - 1 : st - 1)));
        }
        if (++st == STAGES) { st = 0; ph ^= 1; }
      }
      wg_wait<0>();
      reg_fence<128>(acc);
      mbar_arrive_elect(bars + 8 * (STAGES + (st == 0 ? STAGES - 1 : st - 1)));
#pragma unroll
      for (int h = 0; h < 2; h++) {
        if ((tid & 127) == 0) asm volatile("cp.async.bulk.wait_group.read 0;" ::: "memory");
        named_sync(2 + wg, 128);
#pragma unroll
        for (int jj = 0; jj < 8; jj++) {
          const int j = h * 8 + jj;
          const int chunk = (j & 3) * 2 + (lane >> 4);
          stmatrix_x4(cb + (jj >> 2) * 8192 + row * 128 + ((chunk ^ (row & 7)) << 4), pack_bf16(acc[8 * j + 0], acc[8 * j + 1]),
                      pack_bf16(acc[8 * j + 2], acc[8 * j + 3]), pack_bf16(acc[8 * j + 4], acc[8 * j + 5]), pack_bf16(acc[8 * j + 6], acc[8 * j + 7]));
        }
        fence_proxy_async();
        named_sync(2 + wg, 128);
        if ((tid & 127) == 0) {
          tma_store_2d(&tmC, cb, n0 + h * 128, m0 + wg * 64);
          tma_store_2d(&tmC, cb + 8192, n0 + h * 128 + 64, m0 + wg * 64);
          bulk_commit();
        }
      }
    }
    if ((tid & 127) == 0) bulk_wait0();
    KT_END(kid);
  }
}

__global__ void gate_kernel(int blk, unsigned count) {
  unsigned v;
  for (int n = 0; n < SPIN_LIMIT; n++) {
    asm volatile("ld.relaxed.gpu.global.u32 %0, [%1];" : "=r"(v) : "l"(&g_prog[blk]) : "memory");
    if (v >= count) break;
    __nanosleep(400);
  }
}

#define AT_PASS 5
#define AT_NWG 2
constexpr int AT_SMEM = 4 * 16384 + AT_NWG * 4096 + 1024 + 128;
template <int NWG, int STAGES, int MINB>
__global__ void __launch_bounds__(NWG * 128, MINB)
attnA_kernel(const __grid_constant__ CUtensorMap tmQ, const __grid_constant__ CUtensorMap tmKV, bf16* __restrict__ out, int tm0, int h0, int nh, int kid) {
  extern __shared__ __align__(1024) uint8_t smem_raw[];
  constexpr int BK = 128, NT = 2048 / BK, STAGE = 2 * BK * 64;
  const uint32_t sb = s2u(smem_raw);
  const uint32_t sq = sb + STAGES * STAGE;
  const uint32_t ones = sq + NWG * 4096;
  const uint32_t bars = ones + 1024;
  const int tid = threadIdx.x, warp = __shfl_sync(~0u, tid >> 5, 0), lane = tid & 31;
  KT_BEGIN(kid);
  const int head = h0 + blockIdx.x % nh, q0 = (tm0 + blockIdx.x / nh) * NWG * 64;
  constexpr int LAG = 2, PF = STAGES - LAG;
  if (tid == 0) {
    for (int s = 0; s < STAGES; s++) { mbar_init(bars + 8 * s, 1); mbar_init(bars + 8 * (STAGES + s), NWG * 4); }
    mbar_init(bars + 16 * STAGES, 1);
    asm volatile("st.shared.u32 [%0], 0;" ::"r"(bars + 16 * STAGES + 8) : "memory");
    fence_mbar_init();
    mbar_expect_tx(bars + 16 * STAGES, NWG * 4096);
    for (int w = 0; w < NWG; w++) tma_load_2d(sq + w * 4096, &tmQ, head * 32, q0 + w * 64, bars + 16 * STAGES);
    for (int t = 0; t < PF; t++) {
      const uint32_t fb = bars + 8 * t, dst = sb + t * STAGE;
      mbar_expect_tx(fb, STAGE);
      tma_load_2d(dst, &tmKV, 1024 + head * 32, t * BK, fb);
      tma_load_2d(dst + BK * 64, &tmKV, 2048 + head * 32, t * BK, fb);
    }
  }
  if (tid < 256) asm volatile("st.shared.u32 [%0], 0x3F803F80;" ::"r"(ones + tid * 4) : "memory");
  fence_proxy_async();
  __syncthreads();
  const int wg = warp >> 2;
  const float c = 0.17677669529663687f * 1.4426950408889634f;
  float o[20];
#pragma unroll
  for (int i = 0; i < 20; i++) o[i] = 0.f;
  float m0 = -INFINITY, m1 = -INFINITY;
  const uint32_t qd = (((sq + wg * 4096) & 0x3FFFF) >> 4) | (1u << 16);
  const uint32_t kd0 = ((sb & 0x3FFFF) >> 4) | (1u << 16);
  constexpr uint32_t DH = 0x80000020u;
  if (wg == NWG - 1) named_arrive(1, 256);
  mbar_wait(bars + 16 * STAGES, 0);
#pragma unroll 1
  for (int t = 0; t < NT; t++) {
    const int st = t % STAGES;
    mbar_wait(bars + 8 * st, (t / STAGES) & 1);
    const uint32_t kd = kd0 + st * (STAGE >> 4);
    const uint32_t va = (kd & 0xFFFF) + BK * 4, vd = va | ((((ones & 0x3FFFF) >> 4) - va) << 16);
    float s[64];
    wg_fence();
    wgmma_ss_n128_z<0, 0>(s, mkd(qd, DH), mkd(kd, DH));
    wgmma_ss_n128<0, 0>(s, mkd(qd + 2, DH), mkd(kd + 2, DH), 1);
    wg_commit();
    if (warp == 0 && t + PF < NT) {
      const int tt = t + PF, ls = tt % STAGES;
      if (t >= LAG) mbar_wait(bars + 8 * (STAGES + ls), ((t - LAG) / STAGES) & 1);
      if (lane == 0) {
        const uint32_t fb = bars + 8 * ls, dst = sb + ls * STAGE;
        mbar_expect_tx(fb, STAGE);
        tma_load_2d(dst, &tmKV, 1024 + head * 32, tt * BK, fb);
        tma_load_2d(dst + BK * 64, &tmKV, 2048 + head * 32, tt * BK, fb);
      }
      __syncwarp();
    }
    wg_wait<0>();
    reg_fence<64>(s);
    int i0 = __float_as_int(m0), i1 = __float_as_int(m1);
#pragma unroll
    for (int j = 0; j < 16; j++) {
      i0 = __vimax3_s32(i0, __float_as_int(s[4 * j]), __float_as_int(s[4 * j + 1]));
      i1 = __vimax3_s32(i1, __float_as_int(s[4 * j + 2]), __float_as_int(s[4 * j + 3]));
    }
    float x0 = __int_as_float(i0), x1 = __int_as_float(i1);
    if (__any_sync(~0u, (i0 | i1) < 0)) {
      x0 = m0; x1 = m1;
#pragma unroll
      for (int j = 0; j < 16; j++) {
        x0 = fmaxf(x0, fmaxf(s[4 * j], s[4 * j + 1]));
        x1 = fmaxf(x1, fmaxf(s[4 * j + 2], s[4 * j + 3]));
      }
    }
    x0 = fmaxf(x0, __shfl_xor_sync(~0u, x0, 1)); x1 = fmaxf(x1, __shfl_xor_sync(~0u, x1, 1));
    x0 = fmaxf(x0, __shfl_xor_sync(~0u, x0, 2)); x1 = fmaxf(x1, __shfl_xor_sync(~0u, x1, 2));
    const float n0 = x0, n1 = x1;
    const float a0 = ex2((m0 - n0) * c), a1 = ex2((m1 - n1) * c);
    m0 = n0; m1 = n1;
    float b0 = -n0 * c, b1 = -n1 * c;
#pragma unroll
    for (int j = 0; j < 4; j++) { o[4 * j] *= a0; o[4 * j + 1] *= a0; o[4 * j + 2] *= a1; o[4 * j + 3] *= a1; }
    o[16] *= a0; o[18] *= a1;
    {
      uint32_t z;
      named_sync(1 + wg + ((__float_as_uint(a0) | __float_as_uint(a1)) >> 31), 256);
      asm volatile("ld.volatile.shared.u32 %0, [%1];" : "=r"(z) : "r"(bars + 16 * STAGES + 8) : "memory");
      b0 = __uint_as_float(__float_as_uint(b0) ^ z); b1 = __uint_as_float(__float_as_uint(b1) ^ z);
    }
    reg_fence<20>(o);
#pragma unroll
    for (int kk = 0; kk < 8; kk++) {
      uint32_t p[4];
#pragma unroll
      for (int h = 0; h < 2; h++) {
        const int j = 2 * kk + h;
        p[2 * h] = pack_bf16(ex2(fmaf(s[4 * j], c, b0)), ex2(fmaf(s[4 * j + 1], c, b0)));
        p[2 * h + 1] = pack_bf16(ex2(fmaf(s[4 * j + 2], c, b1)), ex2(fmaf(s[4 * j + 3], c, b1)));
      }
      wg_fence();
      wgmma_rs_n40<1>(o, p[0], p[1], p[2], p[3], mkd(vd + kk * 64 - ((kk * 64) << 16), DH), 1);
      if (kk == AT_PASS && !(t == NT - 1 && wg == NWG - 1)) named_arrive(1 + (wg + 1) % NWG, 256);
    }
    wg_commit();
    wg_wait<0>();
    reg_fence<20>(o);
    mbar_arrive_elect(bars + 8 * (STAGES + st));
  }
  const float i0 = 1.f / o[16], i1 = 1.f / o[18];
  const int row = q0 + warp * 16 + (lane >> 2);
  uint32_t* o0 = (uint32_t*)(out + (size_t)row * 1024 + head * 32 + (lane & 3) * 2);
  uint32_t* o1 = o0 + 8 * 512;
#pragma unroll
  for (int j = 0; j < 4; j++) {
    o0[j * 4] = pack_bf16(o[4 * j] * i0, o[4 * j + 1] * i0);
    o1[j * 4] = pack_bf16(o[4 * j + 2] * i1, o[4 * j + 3] * i1);
  }
  KT_END(kid);
}

constexpr int CH_KR = 42;
constexpr int CH_KS = 64 - CH_KR;
#define CH_R0 4350
#define CH_R1 5100
#define CH_G0 5700
#define CH_GK 3
#define CH_WG 8
#define CH_VS 128
#define CH_G1 50
#define CH_WD 200
#define CH_REP 2
constexpr uint32_t SB0 = 1024;
constexpr int OFF_XR = 0;
constexpr int OFF_WS = OFF_XR + 3 * 10240;
constexpr int WS_SZ = CH_KS * 2048;
constexpr int OFF_WO = OFF_WS + 2 * WS_SZ;
constexpr int OFF_XL = OFF_WO + 10 * 8192;
constexpr int OFF_MEM = OFF_WO + 11 * 8192;
constexpr int OFF_OB = OFF_MEM + 8192;
constexpr int OFF_QKV = OFF_MEM + 10240;
constexpr int OFF_SEL = OFF_QKV + 10240;
constexpr int OFF_BAR = OFF_SEL + 128;
constexpr int CH_SMEM = OFF_BAR + 256;
static_assert(CH_SMEM <= 232448, "smem");
__device__ __forceinline__ uint32_t piece_off(int h, int r) { return (r >> 1) * 64 + ((h ^ (r >> 2)) & 1) * 32 + (r & 1) * 16; }
__host__ __device__ constexpr int sl_off(int r, int j) { return OFF_XR + 4096 + (j < 2 ? r * 5120 + j * 512 : 10240 + r * 256); }
constexpr int B_XF = 0, B_XE = 3, B_R = 6, B_G = 9, B_P0 = 12, B_P1 = 13, B_P2 = 14, B_SM = 15, B_SX = 16, B_O = 17, B_LF = 18, B_FLAG = 19, B_T = 20, B_BASE = 21, B_P3 = 22, B_C = 23;

__device__ uint4 g_part[2][64][32][16];
__device__ uint4 g_memx[4][CH_REP][1024 + 72];
__device__ uint32_t g_ts[4][96 * 8];
#define PROF_T(i)
#define PROF_V(i, v)

__device__ __forceinline__ uint4 ld_poll4(const void* p) {
  uint4 v;
  asm volatile("ld.relaxed.gpu.global.v4.u32 {%0,%1,%2,%3}, [%4];" : "=r"(v.x), "=r"(v.y), "=r"(v.z), "=r"(v.w) : "l"(p) : "memory");
  return v;
}
__device__ __forceinline__ uint2 ld_poll2(const void* p) {
  uint2 v;
  asm volatile("ld.relaxed.gpu.global.v2.u32 {%0,%1}, [%2];" : "=r"(v.x), "=r"(v.y) : "l"(p) : "memory");
  return v;
}
__device__ __forceinline__ uint32_t ld_poll1(const void* p) {
  uint32_t v;
  asm volatile("ld.relaxed.gpu.global.u32 %0, [%1];" : "=r"(v) : "l"(p) : "memory");
  return v;
}
__device__ __forceinline__ void st_pub4(void* p, uint4 v) { asm volatile("st.relaxed.gpu.global.v4.u32 [%0], {%1,%2,%3,%4};" ::"l"(p), "r"(v.x), "r"(v.y), "r"(v.z), "r"(v.w) : "memory"); }
__device__ __forceinline__ void st_pub2(void* p, uint32_t a, uint32_t b) { asm volatile("st.relaxed.gpu.global.v2.u32 [%0], {%1,%2};" ::"l"(p), "r"(a), "r"(b) : "memory"); }
__device__ __forceinline__ void st_pub1(void* p, uint32_t v) { asm volatile("st.relaxed.gpu.global.u32 [%0], %1;" ::"l"(p), "r"(v) : "memory"); }
__device__ __forceinline__ void st_async2(uint32_t a, float x, float y, uint32_t mb) {
  asm volatile("st.async.weak.shared::cluster.mbarrier::complete_tx::bytes.v2.f32 [%0], {%1,%2}, [%3];" ::"r"(a), "f"(x), "f"(y), "r"(mb) : "memory");
}
__device__ __forceinline__ void st_async4(uint32_t a, uint32_t x, uint32_t y, uint32_t z, uint32_t w, uint32_t mb) {
  asm volatile("st.async.weak.shared::cluster.mbarrier::complete_tx::bytes.v4.b32 [%0], {%1,%2,%3,%4}, [%5];" ::"r"(a), "r"(x), "r"(y), "r"(z), "r"(w), "r"(mb) : "memory");
}
__device__ __forceinline__ void mbar_arrive_elect_if(uint32_t a, bool on) {
  asm volatile("{.reg .pred p, q; elect.sync _|p, 0xffffffff; setp.ne.and.u32 q, %1, 0, p; @q mbarrier.arrive.shared::cluster.b64 _, [%0];}" ::"r"(a), "r"((uint32_t)on) : "memory");
}
__device__ __forceinline__ void mbar_arrive_remote(uint32_t b, uint32_t r, uint32_t who) {
  asm volatile("{.reg .pred p; .reg .u32 a; setp.eq.u32 p, %2, 0; mapa.shared::cluster.u32 a, %0, %1; @p mbarrier.arrive.shared::cluster.b64 _, [a];}"
               ::"r"(b), "r"(r), "r"(who) : "memory");
}
__device__ __forceinline__ void mbar_expect_remote(uint32_t b, uint32_t bytes) { asm volatile("mbarrier.arrive.expect_tx.shared::cluster.b64 _, [%0], %1;" ::"r"(b), "r"(bytes) : "memory"); }
__device__ __forceinline__ void tma_prefetch_2d(const CUtensorMap* tm, int c0, int c1) {
  asm volatile("cp.async.bulk.prefetch.tensor.2d.L2.global [%0, {%1, %2}];" ::"l"(tm), "r"(c0), "r"(c1) : "memory");
}
__device__ __forceinline__ uint32_t nz(uint32_t w) { return w == 0u ? 0x80000000u : w; }
__device__ __forceinline__ uint4 lds128(uint32_t a) {
  uint4 v;
  asm volatile("ld.shared.v4.u32 {%0,%1,%2,%3}, [%4];" : "=r"(v.x), "=r"(v.y), "=r"(v.z), "=r"(v.w) : "r"(a) : "memory");
  return v;
}
__device__ __forceinline__ float4 lds128f(uint32_t a) {
  float4 v;
  asm volatile("ld.shared.v4.f32 {%0,%1,%2,%3}, [%4];" : "=f"(v.x), "=f"(v.y), "=f"(v.z), "=f"(v.w) : "r"(a) : "memory");
  return v;
}
__device__ __forceinline__ float2 lds64f(uint32_t a) {
  float2 v;
  asm volatile("ld.shared.v2.f32 {%0,%1}, [%2];" : "=f"(v.x), "=f"(v.y) : "r"(a) : "memory");
  return v;
}
__device__ __forceinline__ uint32_t lds32(uint32_t a) {
  uint32_t v;
  asm volatile("ld.shared.u32 %0, [%1];" : "=r"(v) : "r"(a) : "memory");
  return v;
}
__device__ __forceinline__ uint2 lds64(uint32_t a) {
  uint2 v;
  asm volatile("ld.shared.v2.u32 {%0,%1}, [%2];" : "=r"(v.x), "=r"(v.y) : "r"(a) : "memory");
  return v;
}
__device__ __forceinline__ bool named_sync_or(int id, int n, bool v) {
  uint32_t r;
  asm volatile("{.reg .pred p, q; setp.ne.u32 p, %3, 0; bar.red.or.pred q, %1, %2, p; selp.u32 %0, 1, 0, q;}" : "=r"(r) : "r"(id), "r"(n), "r"((uint32_t)v) : "memory");
  return __any_sync(~0u, r);
}
__device__ __forceinline__ void sts128(uint32_t a, uint4 v) { asm volatile("st.shared.v4.u32 [%0], {%1,%2,%3,%4};" ::"r"(a), "r"(v.x), "r"(v.y), "r"(v.z), "r"(v.w) : "memory"); }
__device__ __forceinline__ void sts64(uint32_t a, uint2 v) { asm volatile("st.shared.v2.u32 [%0], {%1,%2};" ::"r"(a), "r"(v.x), "r"(v.y) : "memory"); }
__device__ __forceinline__ void sts32(uint32_t a, uint32_t v) { asm volatile("st.shared.u32 [%0], %1;" ::"r"(a), "r"(v) : "memory"); }

__device__ __forceinline__ void chain_xsoftmax(uint32_t sb, int w, int lane) {
  const float c = 0.08838834764831845f * 1.4426950408889634f;
  const int g = lane >> 2, t = lane & 3;
  float sc[5][2];
  const uint32_t xl = sb + OFF_XL + (w & 2 ? 1536 : 0) + lane * 16 + (w & 1) * 8;
#pragma unroll
  for (int j = 0; j < 5; j++) {
    sc[j][0] = sc[j][1] = -INFINITY;
    if (j <= w + 1) {
      const float2 a = lds64f(xl + j * 512), b = lds64f(xl + 4096 + j * 512);
      if (j <= w || 2 * t <= g) sc[j][0] = a.x + b.x;
      if (j <= w || 2 * t + 1 <= g) sc[j][1] = a.y + b.y;
    }
  }
  float m = fmaxf(fmaxf(fmaxf(sc[0][0], sc[0][1]), fmaxf(sc[1][0], sc[1][1])), fmaxf(fmaxf(sc[2][0], sc[2][1]), fmaxf(sc[3][0], sc[3][1])));
  m = fmaxf(m, fmaxf(sc[4][0], sc[4][1]));
  m = fmaxf(m, __shfl_xor_sync(~0u, m, 1));
  m = fmaxf(m, __shfl_xor_sync(~0u, m, 2));
  const float bb = -m * c;
  float l = 0.f;
#pragma unroll
  for (int j = 0; j < 5; j++) {
    sc[j][0] = ex2(fmaf(sc[j][0], c, bb)); sc[j][1] = ex2(fmaf(sc[j][1], c, bb));
    l += sc[j][0] + sc[j][1];
  }
  l += __shfl_xor_sync(~0u, l, 1);
  l += __shfl_xor_sync(~0u, l, 2);
  const float il = __fdividef(1.f, l);
  const uint32_t pa = sb + OFF_MEM + w * 768 + lane * 4;
#pragma unroll
  for (int j = 0; j < 5; j++) sts32(pa + j * 128, pack_bf16(sc[j][0] * il, sc[j][1] * il));
  sts32(pa + 640, 0u);
  fence_proxy_async();
}

__device__ __forceinline__ void bulk_g2s(uint32_t dst, const void* src, uint32_t bytes, uint32_t mb) {
  asm volatile("cp.async.bulk.shared::cluster.global.mbarrier::complete_tx::bytes [%0], [%1], %2, [%3];" ::"r"(dst), "l"(src), "r"(bytes), "r"(mb) : "memory");
}
__device__ __forceinline__ float rcp_fast(float x) {
  float y;
  asm("rcp.approx.ftz.f32 %0, %1;" : "=f"(y) : "f"(x));
  return y;
}
__device__ __forceinline__ int read_lane() {
  int l;
  asm volatile("mov.u32 %0, %%laneid;" : "=r"(l));
  return l;
}
__device__ __forceinline__ void spin_clocks(uint32_t t0, int d) {
  while (__any_sync(~0u, (int)((uint32_t)clock() - t0) < d)) {}
}

__device__ __forceinline__ void mem_check(uint32_t sb, int t128, uint32_t& gph, const uint8_t* src, int lf) {
  const uint32_t gb = sb + OFF_BAR + 8 * B_G, a = sb + OFF_MEM + t128 * 16;
  uint32_t seen = 0;
  int n = 0;
  mbar_wait(gb, gph);
  while (true) {
    gph ^= 1;
#pragma unroll
    for (int i = 0; i < 5; i++) {
      const uint4 u = lds128(a + i * 2048);
      seen |= ((u.x != 0) | (u.y != 0) << 1 | (u.z != 0) << 2 | (u.w != 0) << 3) << (4 * i);
    }
    const bool bad = named_sync_or(5, 128, seen != 0xFFFFFu);
    if (t128 == 0) { sts32(sb + OFF_BAR + 8 * B_FLAG, bad); mbar_arrive(sb + OFF_BAR + 8 * B_C); }
    if (!bad) break;
    named_sync(2, 384);
    if (t128 == 0) { mbar_expect_tx(gb, 10240); bulk_g2s(sb + OFF_MEM, src, 10240, gb); }
    __syncwarp();
    mbar_wait(gb, gph);
#pragma unroll 1
    for (int i = 0; i < 20; i++)
      if ((seen >> i) & 1) sts32(a + (i >> 2) * 2048 + (i & 3) * 4, 0u);
    fence_proxy_async();
    named_sync(9, 384);
    if (++n > SPIN_LIMIT) __trap();
  }
  if (lf >= 0) mbar_wait(sb + OFF_BAR + 8 * B_LF, lf);
  named_sync(2, 384);
}
__device__ __forceinline__ uint32_t wo_addr(uint32_t sb, int blk, int lane) {
  const int krow = (lane >> 4) * 8 + (lane & 7);
  return sb + OFF_WO + blk * 8192 + krow * 64 + (((((lane >> 3) & 1)) ^ ((krow >> 1) & 3)) << 4);
}
__device__ __forceinline__ void wo_publish(uint2* __restrict__ dst, const float* d) {
  st_pub2(dst, nz(movmatrix_t(pack_bf16(d[0], d[1]))), nz(movmatrix_t(pack_bf16(d[2], d[3]))));
}
__device__ __forceinline__ void chain_wo_first(uint32_t sb, int s, uint32_t wa0, int lane, bool first, uint2* __restrict__ dst) {
  constexpr int PF = 5;
  const uint32_t wa1 = wa0 ^ 32;
  uint32_t a[PF][4];
#pragma unroll
  for (int f = 0; f < PF; f++) ldmatrix_x4_t(((f & 1) ? wa1 : wa0) + (f >> 1) * 1024, a[f][0], a[f][1], a[f][2], a[f][3]);
  mbar_wait(sb + OFF_BAR + 8 * B_O, s & 1);
  float d[4][4];
#pragma unroll
  for (int i = 0; i < 4; i++) d[i][0] = d[i][1] = d[i][2] = d[i][3] = 0.f;
  uint4 ob;
#pragma unroll
  for (int f = 0; f < 16; f++) {
    if ((f & 3) == 0) ob = lds128(sb + OFF_OB + (f >> 2) * 512 + lane * 16);
    const uint32_t b0 = (f & 2) ? ob.z : ob.x, b1 = (f & 2) ? ob.w : ob.y;
    mma16816(d[f & 3], a[f % PF][0], a[f % PF][1], a[f % PF][2], a[f % PF][3], b0, b1);
    if (f + PF < 16)
      ldmatrix_x4_t((((f + PF) & 1) ? wa1 : wa0) + ((f + PF) >> 1) * 1024, a[f % PF][0], a[f % PF][1], a[f % PF][2], a[f % PF][3]);
    if (f == CH_WG && first) named_arrive(10, 384);
  }
#pragma unroll
  for (int i = 0; i < 4; i++) { d[0][i] += d[2][i]; d[1][i] += d[3][i]; }
  wo_publish(dst, d[0]);
  wo_publish(dst + 1024, d[1]);
}
__device__ __forceinline__ void chain_wo_tile(uint32_t sb, int s, uint32_t wa, uint32_t oa, uint2* __restrict__ dst, int psw, float* spare) {
  uint32_t a[3][4];
  uint4 ob[2];
#pragma unroll
  for (int f = 0; f < 3; f++) ldmatrix_x4_t(wa + f * 1024, a[f][0], a[f][1], a[f][2], a[f][3]);
  named_sync(10, 384);
  ob[0] = lds128(oa);
  ob[1] = lds128(oa + 512);
  float(&d)[4] = *(float(*)[4])spare;
  d[0] = d[1] = d[2] = d[3] = 0.f;
#pragma unroll
  for (int f = 0; f < 8; f++) {
    const uint4 o = ob[(f >> 1) & 1];
    mma16816v(d, a[f % 3][0], a[f % 3][1], a[f % 3][2], a[f % 3][3], (f & 1) ? o.z : o.x, (f & 1) ? o.w : o.y);
    if (f + 3 < 8) ldmatrix_x4_t(wa + (f + 3) * 1024, a[f % 3][0], a[f % 3][1], a[f % 3][2], a[f % 3][3]);
    if (f == 1 || f == 3) ob[f >> 1] = lds128(oa + 1024 + (f >> 1) * 512);
    if (f == 4) dst += read_lane() ^ psw;
  }
  wo_publish(dst, d);
}

#define CH_IDS int head, rank; \
  asm volatile("mov.u32 %0, %%clusterid.x;" : "=r"(head)); \
  asm volatile("mov.u32 %0, %%cluster_ctarank;" : "=r"(rank))

__global__ void __cluster_dims__(3, 1, 1) __launch_bounds__(512, 1)
chain_kernel(const __grid_constant__ CUtensorMap tmWq, const __grid_constant__ CUtensorMap tmWk, const __grid_constant__ CUtensorMap tmWv,
             const __grid_constant__ CUtensorMap tmWo, const __grid_constant__ CUtensorMap tmX, const __grid_constant__ CUtensorMap tmOB,
             const bf16* __restrict__ mem0) {
  extern __shared__ __align__(1024) uint8_t smem_raw[];
  const uint32_t sb = s2u(smem_raw);
  const uint32_t bars = sb + OFF_BAR;
  const int tid = threadIdx.x, warp = __shfl_sync(~0u, tid >> 5, 0), wg = warp >> 2;
  int lane = tid & 31;
  KT_BEGIN(0);
  if (tid == 0) {
    const int rank = blockIdx.x % 3;
    if ((sb & 0x3FFFF) != SB0) __trap();
    for (int i = 0; i < 3; i++) { mbar_init(bars + 8 * (B_XF + i), 1); mbar_init(bars + 8 * (B_XE + i), 24); }
    mbar_init(bars + 8 * B_R, 1); mbar_init(bars + 8 * B_T, 1); mbar_init(bars + 8 * B_C, 1);
    mbar_init(bars + 8 * B_P0, 1); mbar_init(bars + 8 * B_P1, 1); mbar_init(bars + 8 * B_P2, 1); mbar_init(bars + 8 * B_P3, 1);
    mbar_init(bars + 8 * B_SM, 1); mbar_init(bars + 8 * B_SX, 1); mbar_init(bars + 8 * B_O, rank == 2 ? 4 : 1); mbar_init(bars + 8 * B_LF, 1);
    for (int i = 0; i < 3; i++) mbar_init(bars + 8 * (B_G + i), 1);
    fence_mbar_init();
  }
  __syncthreads();

  if (wg < 2) {
    asm volatile("setmaxnreg.inc.sync.aligned.u32 216;");
    CH_IDS;
    uint2* const pdst = (uint2*)&g_part[0][rank * 2][head][0];
    const int psw = ((head & 1) << 3) | ((head & 2) << 1);
    uint32_t w[CH_KR][4];
    const uint32_t wlane = (((lane >> 4) * 8 + (lane & 7)) * 128) + ((((warp & 3) * 2 + ((lane >> 3) & 1)) ^ (lane & 7)) << 4);
    cluster_sync_all();
    mbar_wait(bars + 8 * B_P0, 0);
    KT_END(6);
#pragma unroll
    for (int k = 0; k < 22; k++) ldmatrix_x4_t(sb + OFF_WO + wg * 45056 + wlane + k * 2048, w[k][0], w[k][1], w[k][2], w[k][3]);
    named_arrive(11, 288);
    mbar_wait(bars + 8 * B_P1, 0);
#pragma unroll
    for (int k = 22; k < CH_KR; k++) ldmatrix_x4_t(sb + OFF_WO + wg * 45056 + wlane + (k - 22) * 2048, w[k][0], w[k][1], w[k][2], w[k][3]);
    named_arrive(12, 288);
    uint32_t wsd = (((SB0 + OFF_WS) >> 4) + wg * (WS_SZ >> 4)) | (64u << 16);
    const uint32_t qrow = sb + OFF_QKV + warp * 1280;
    uint32_t xd0 = (((SB0 + OFF_XR) >> 4) | (1u << 16)), xd1 = xd0 + 640, xd2 = xd0 + 1280;
    uint32_t xf0 = bars + 8 * B_XF, xf1 = xf0 + 8, xf2 = xf0 + 16;
    uint32_t xe0 = mapa(bars + 8 * B_XE, 0), xe1 = mapa(bars + 8 * B_XE + 8, 1), xe2 = mapa(bars + 8 * B_XE + 16, 2);
    uint32_t pm = 0xE38E38u;
    KT_END(7);
    mbar_wait(bars + 8 * B_P2, 0);
    KT_END(8);
    uint32_t pk[8] = {0, 0, 0, 0, 0, 0, 0, 0};
    const uint2* src = (const uint2*)&g_memx[0][0][0];
    uint32_t base = 0;
#pragma unroll 1
    for (int s = -1;; s++) {
      uint32_t ready = 0, gtok = 0;
      if (s > 0 && s < 64) {
        spin_clocks(base, CH_G0);
        PROF_T(22);
      }
      uint2 x[3];
#pragma unroll
      for (int i = 0; i < 3; i++) x[i] = ld_poll2(src + i * 256);
      lane = read_lane();
      const uint32_t ea = qrow + ((lane >> 3) & 1) * 640 + 128 + (lane >> 4) * 128 + (lane & 7) * 16;
      uint32_t ma = sb + OFF_MEM + (lane >> 4) * 256 + piece_off(lane >> 3, lane & 7);
      uint32_t mg = sb - SB0 + ((xd2 & 0xFFFF) << 4) + 9216 + (lane & 7) * 128 + (((4 + (lane >> 3)) ^ (lane & 7)) << 4);
      const int pr = (lane >> 3) * 2 + ((lane >> 1) & 1), ph = ((lane >> 2) ^ (lane >> 4)) & 1;
      uint32_t mo = sb - SB0 + 4096 + wg * 5120 + pr * 128 + ((((warp & 3) * 2 + ph) ^ pr) << 4) + (lane & 1) * 8;
      if (s > 0 && rank == 2) {
        float o[16];
        const uint32_t vd = (((SB0 + OFF_QKV) >> 4) + wg * 320) | (8u << 16), pd = ((SB0 + OFF_MEM) >> 4) | (8u << 16);
        named_sync(4, 384);
        wg_fence();
        wgmma_ss_n32_z<0, 0>(o, mkd(vd, 40u), mkd(pd, 48u));
        wgmma_ss_n32<0, 0>(o, mkd(vd + 16, 40u), mkd(pd + 16, 48u), 1);
        wgmma_ss_n32<0, 0>(o, mkd(vd + 32, 40u), mkd(pd + 32, 48u), 1);
        wg_commit();
        const uint32_t oa = sb + OFF_XL + wg * 4096 + ((lane >> 4) * 8 + (lane & 7)) * 128 + ((((warp & 3) * 2 + ((lane >> 3) & 1)) ^ (lane & 7)) << 4);
        wg_wait<0>();
        reg_fence<16>(o);
        stmatrix_x4_t(oa, pack_bf16(o[0], o[1]), pack_bf16(o[2], o[3]), pack_bf16(o[4], o[5]), pack_bf16(o[6], o[7]));
        stmatrix_x4_t(oa + 2048, pack_bf16(o[8], o[9]), pack_bf16(o[10], o[11]), pack_bf16(o[12], o[13]), pack_bf16(o[14], o[15]));
        if (s == 64) {
          fence_proxy_async();
          named_arrive(13, 288);
        }
      }
      if (s == 64) break;
      stmatrix_x4(ea, pk[0], pk[1], pk[2], pk[3]);
      stmatrix_x4(ea + 256, pk[4], pk[5], pk[6], pk[7]);
      ma = __shfl_sync(~0u, ma, lane); mg = __shfl_sync(~0u, mg, lane);
      mo = __shfl_sync(~0u, mo, lane);
      mbar_wait(xf0, pm & 1);
      if (s > 0) {
        int n = 0;
        while (true) {
          bool bad = false;
#pragma unroll
          for (int i = 0; i < 3; i++) {
            const bool b = (x[i].x == 0u) | (x[i].y == 0u);
            if (b) x[i] = ld_poll2(src + i * 256);
            bad |= b;
          }
          if (!__any_sync(~0u, bad)) break;
          if (++n > SPIN_LIMIT) __trap();
        }
        sts64(mo + ((xd0 & 0xFFFF) << 4), x[0]); sts64(mo + ((xd1 & 0xFFFF) << 4), x[1]); sts64(mo + ((xd2 & 0xFFFF) << 4), x[2]);
        fence_proxy_async();
        if (rank == 2) named_arrive(13, 288);
        if (warp == 0) PROF_V(16, n);
      }
      if (s >= 0) named_sync(1, 288);
      if (s == 0) KT_END(1);
      float acc[20];
      uint32_t wta = 0, oba = 0;
#pragma unroll
      for (int c = 0; c < 8; c++) {
        const int j = c % 3, pj = (c + 2) % 3, nj = (c + 1) % 3;
        bool released = false;
        if (c == 3) {
          mbar_wait_tok(bars + 8 * B_G, pm >> 31, gtok);
          uint32_t bq[3][4];
          ldmatrix_x4(mg, bq[0][0], bq[0][1], bq[0][2], bq[0][3]);
          ldmatrix_x4(ma, bq[1][0], bq[1][1], bq[1][2], bq[1][3]);
          ldmatrix_x4(ma + 512, bq[2][0], bq[2][1], bq[2][2], bq[2][3]);
          wg_wait<0>();
          reg_fence<20>(acc);
          mbar_arrive_elect(xe1);
          mbar_arrive_elect(xe2);
          released = true;
          if (s >= 0) {
            PROF_T(0);
            float d1[4] = {0.f, 0.f, 0.f, 0.f}, d2[4] = {0.f, 0.f, 0.f, 0.f};
            float(&d0)[4] = *(float(*)[4]) & acc[16];
            int n = 0;
            bool redo;
            while (true) {
#pragma unroll
              for (int k = 0; k < CH_KR / 2; k++) {
                const int q = k % 3, ca = (2 * k) % 3, cb = (2 * k + 1) % 3;
                mma16816(ca == 0 ? d1 : ca == 1 ? d2 : d0, w[2 * k][0], w[2 * k][1], w[2 * k][2], w[2 * k][3], bq[q][0], bq[q][1]);
                mma16816(cb == 0 ? d1 : cb == 1 ? d2 : d0, w[2 * k + 1][0], w[2 * k + 1][1], w[2 * k + 1][2], w[2 * k + 1][3], bq[q][2], bq[q][3]);
                if (k + 3 < CH_KR / 2) ldmatrix_x4(ma + (k + 2) * 512, bq[q][0], bq[q][1], bq[q][2], bq[q][3]);
                if (k == 18) {
                  lane = read_lane();
                  mbar_wait(bars + 8 * B_C, pm >> 31);
                  redo = __any_sync(~0u, lds32(bars + 8 * B_FLAG));
                  ready = mbar_try(xf0, (pm >> 3) & 1);
                }
                if (k == 2 && rank == 2 && n == 0) named_arrive(7, 288);
              }
              const uint32_t qa = qrow + lane * 4;
              sts32(qa, pack_bf16(d0[0] + d1[0] + d2[0], d0[1] + d1[1] + d2[1]));
              sts32(qa + 640, pack_bf16(d0[2] + d1[2] + d2[2], d0[3] + d1[3] + d2[3]));
              fence_proxy_async();
              named_arrive(2, 384);
              pm ^= 0x80000000u;
              if (__builtin_expect(!redo, 1)) break;
              named_sync(9, 384);
              bq[0][0] = bq[0][1] = bq[0][2] = bq[0][3] = 0u;
              ldmatrix_x4(ma, bq[1][0], bq[1][1], bq[1][2], bq[1][3]);
              ldmatrix_x4(ma + 512, bq[2][0], bq[2][1], bq[2][2], bq[2][3]);
              if (++n > SPIN_LIMIT) __trap();
            }
            PROF_T(9);
            if (warp == 0) PROF_V(17, n);
            if (s == 63) {
#pragma unroll
              for (int i = 0; i < 8; i++) pk[i] = 0;
              src = (const uint2*)&g_memx[0][0][0];
              base = 0;
              goto next;
            }
            wta = __shfl_sync(~0u, wo_addr(sb, (rank == 2 ? 6 : 7) + (warp >> 1), lane) ^ ((warp & 1) * 32), lane);
            oba = __shfl_sync(~0u, sb + OFF_OB + lane * 16, lane);
            if (rank < 2) named_sync(4, 416);
          }
          if (s < 0) ready = 0;
        }
        if (c == 4 && s >= 0 && rank == 2) {
          wg_wait<0>();
          mbar_arrive_elect(xe0);
          released = true;
          named_sync(6, 384);
        }
        if ((c == 5 || c == 6) && s >= 0 && (c == 5) == (rank == 2)) {
          const int blk = (rank == 2 ? 6 : 7) + (warp >> 1);
          wg_wait<0>();
          reg_fence<20>(acc);
          mbar_arrive_elect(pj == 0 ? xe0 : pj == 1 ? xe1 : xe2);
          released = true;
          PROF_T(10);
          chain_wo_tile(sb, s, wta, oba, pdst + (s & 1) * 65536 + blk * 6144 + (warp & 1) * 1024, psw, &acc[16]);
          PROF_T(1);
          named_sync(3, 384);
        }
        if (c == 7 && s >= 0) PROF_T(11);
        if (c == 7) {
          src = (const uint2*)&g_memx[s & 3][head % CH_REP][0] + warp * 32 + read_lane();
          if (s >= 0) mbar_wait(bars + 8 * B_T, s & 1);
          base = lds32(bars + 8 * B_BASE);
        }
        if (c > 0) mbar_wait_tok(j == 0 ? xf0 : j == 1 ? xf1 : xf2, (pm >> c) & 1, ready);
        if (c == 0 && s >= 0) PROF_T(8);
        if (c != 2 && c != 7)
          ready = mbar_try(nj == 0 ? xf0 : nj == 1 ? xf1 : xf2, (pm >> (c + 1)) & 1);
        uint32_t xd = j == 0 ? xd0 : j == 1 ? xd1 : xd2;
        asm volatile("" : "+r"(xd), "+r"(wsd));
        if (c == 3 || c == 5 || c == 6) reg_fence<20>(acc);
        wg_fence();
#pragma unroll
        for (int kk = 0; kk < 8; kk++) {
          const int k = c * 8 + kk;
          const uint32_t xo = (kk >> 2) * 320 + (kk & 3) * 2;
          if (k >= CH_KS) {
            const int kr = k >= CH_KS ? k - CH_KS : 0;
            wgmma_rs_n32<0>(acc, w[kr][0], w[kr][1], w[kr][2], w[kr][3], mkd(xd + xo, 0x40000040u), 1);
          } else {
            if (k == 0) wgmma_ss_n40_z<1, 0>(acc, mkd(wsd, 0x40000040u), mkd(xd, 0x40000040u));
            else wgmma_ss_n40<1, 0>(acc, mkd(wsd + k * 128, 0x40000040u), mkd(xd + xo, 0x40000040u), 1);
          }
          if (c == 2 && kk == CH_GK) gtok = mbar_try(bars + 8 * B_G, pm >> 31);
          if (kk == 1 && c > 3) {
            wg_commit();
            wg_wait<1>();
            mbar_arrive_elect_if(pj == 0 ? xe0 : pj == 1 ? xe1 : xe2, !released);
          }
        }
        wg_commit();
        if (c == 1) {
          wg_wait<1>();
          mbar_arrive_elect(xe0);
        }
      }
      wg_wait<0>();
      reg_fence<16>(acc);
      mbar_arrive_elect(xe1);
      if (s >= 0) PROF_T(12);
      {
        uint32_t t;
        t = xd2; xd2 = xd1; xd1 = xd0; xd0 = t;
        t = xf2; xf2 = xf1; xf1 = xf0; xf0 = t;
        t = xe2; xe2 = xe1; xe1 = xe0; xe0 = t;
        pm = (((pm >> 8) & 0xFFFFu) | ((pm & 0xFFu) << 16)) | (pm & 0x80000000u);
      }
#pragma unroll
      for (int i = 0; i < 8; i++) pk[i] = pack_bf16(acc[2 * i], acc[2 * i + 1]);
    next:;
    }
    cluster_sync_all();
    KT_END(0);
  } else if (wg == 2) {
    asm volatile("setmaxnreg.dec.sync.aligned.u32 56;");
    CH_IDS;
    uint2* const pdst = (uint2*)&g_part[0][rank * 2][head][0];
    const int psw = ((head & 1) << 3) | ((head & 2) << 1);
    const int w = warp & 3;
    int t128 = __shfl_sync(~0u, tid & 127, lane);
    if (t128 < 32) sts32(sb + OFF_SEL + t128 * 4, (t128 & 4) ? 0x3F800000u : 0x00003F80u);
    cluster_sync_all();
#pragma unroll 2
    for (int i = 0; i < 8; i++) {
      const int pc = t128 + i * 128;
      const int b = pc >> 3, r = pc & 7, ch = b >> 3;
      const uint32_t dst = b >= 48 ? OFF_MEM - 6144 + (b >> 1) * 256 + piece_off(b, r)
                                   : OFF_XR + ((2 + (ch >> 1)) % 3) * 10240 + (ch & 1) * 5120 + 4096 + r * 128 + (((b & 7) ^ r) << 4);
      const uint4 v = *(const uint4*)(mem0 + r * 1024 + b * 8);
      sts128(sb + dst, make_uint4(nz(v.x), nz(v.y), nz(v.z), nz(v.w)));
    }
    fence_proxy_async();
    named_sync(5, 128);
    if (t128 == 0) mbar_arrive(bars + 8 * B_G);
    uint32_t rph = 0, gph = 0;
    mbar_wait(bars + 8 * B_P3, 0);
    if (rank < 2) {
      const uint32_t rsb = mapa(sb, 2);
      const int red = head * 2 + rank;
#pragma unroll 1
      for (int s = 0; s < 64; s++) {
        asm volatile("" : "+r"(t128));
        lane = t128 & 31;
        if (t128 == 0 && s < 63) mbar_expect_tx(bars + 8 * B_O, 2048);
        mem_check(sb, t128, gph, (const uint8_t*)&g_memx[(s - 1) & 3][head % CH_REP][0] + 6144, s & 1);
        {
          float sc[20];
          const uint32_t qd = ((SB0 + OFF_QKV - 128) >> 4) | (40u << 16), kd = ((SB0 + OFF_QKV + 5120) >> 4) | (40u << 16);
          wg_fence();
#pragma unroll
          for (int ks = 0; ks < 4; ks++) {
            if (ks == 0) wgmma_ss_n40_z<1, 1>(sc, mkd(qd, 8u), mkd(kd, 8u));
            else wgmma_ss_n40<1, 1>(sc, mkd(qd + ks * 80, 8u), mkd(kd + ks * 80, 8u), 1);
          }
          wg_commit();
          wg_wait<0>();
          reg_fence<20>(sc);
          PROF_T(2);
          if (w == 0) {
            if (s < 63) {
              const uint32_t mb = rsb + OFF_BAR + 8 * B_SM;
              st_async4(rsb + sl_off(rank, 0) + lane * 16, __float_as_uint(sc[2]), __float_as_uint(sc[3]), __float_as_uint(sc[6]), __float_as_uint(sc[7]), mb);
              st_async4(rsb + sl_off(rank, 1) + lane * 16, __float_as_uint(sc[10]), __float_as_uint(sc[11]), __float_as_uint(sc[14]), __float_as_uint(sc[15]), mb);
              st_async2(rsb + sl_off(rank, 2) + lane * 8, sc[18], sc[19], mb);
            }
            named_arrive(5, 96);
          } else if (w < 3) {
            named_sync(5, 96);
            const uint32_t dst = rsb + OFF_XL + rank * 4096 + (w == 2 ? 1536 : 0) + lane * 16;
#pragma unroll
            for (int j = 0; j < 5; j++)
              if (j < 3 || w == 2)
                st_async4(dst + j * 512, __float_as_uint(sc[4 * j]), __float_as_uint(sc[4 * j + 1]), __float_as_uint(sc[4 * j + 2]),
                          __float_as_uint(sc[4 * j + 3]), rsb + OFF_BAR + 8 * B_SX);
          }
        }
        PROF_T(3);
        if (s == 63) break;
        named_arrive(4, 416);
        PROF_T(4);
#pragma unroll 1
        for (int blk = w;; blk += 3) {
          chain_wo_first(sb, s, wo_addr(sb, blk, lane), lane, blk < 4, pdst + (s & 1) * 65536 + blk * 6144 + (lane ^ psw));
          if (blk == 0 || blk > 3) break;
        }
        named_arrive(3, 384);
        PROF_T(6);
        const int g = lane >> 2, t = lane & 3;
        int n = 0;
        const uint32_t ra = sb + OFF_MEM + t * 256 + (((w * 8 + g) ^ ((t & 1) << 3) ^ ((t & 2) << 1)) * 8);
        uint8_t* const md = (uint8_t*)&g_memx[s & 3][t >> 1][red * 16] + piece_off(t, w * 2 + (g >> 2)) + (g & 3) * 4;
        if (w == 0) {
          mbar_wait(bars + 8 * B_T, s & 1);
          spin_clocks(lds32(bars + 8 * B_BASE), red < 24 ? CH_R0 : CH_R1);
        }
        PROF_T(20);
        while (true) {
          if (t128 == 0) { mbar_expect_tx(bars + 8 * B_R, 8192); bulk_g2s(sb + OFF_MEM, &g_part[s & 1][red][0][0], 8192, bars + 8 * B_R); }
          __syncwarp();
          mbar_wait(bars + 8 * B_R, rph);
          rph ^= 1;
          if (n == 0) PROF_T(21);
          uint2 x[8];
#pragma unroll
          for (int i = 0; i < 8; i++) x[i] = lds64(ra + i * 1024);
          float d[4];
          const uint64_t sd = mkd((SB0 + OFF_SEL) >> 4, 0u);
          wg_fence();
#pragma unroll
          for (int i = 0; i < 4; i++) wgmma_rs_n8<0>(d, x[2 * i].x, x[2 * i].y, x[2 * i + 1].x, x[2 * i + 1].y, sd, i != 0);
          wg_commit();
          uint32_t mn = 0xFFFFFFFFu;
#pragma unroll
          for (int i = 0; i < 8; i++) mn = min(mn, min(x[i].x, x[i].y));
          const bool bad = __any_sync(~0u, mn == 0u);
          wg_wait<0>();
          reg_fence<4>(d);
          const bool hb = t & 1;
          if (!bad) st_pub1(md, nz(pack_bf16(hb ? d[2] : d[0], hb ? d[3] : d[1])));
          PROF_T(5);
          if (!named_sync_or(5, 128, bad)) break;
          if (++n > SPIN_LIMIT) __trap();
        }
        named_arrive(8, 192);
        if (w == 0) PROF_V(19, n);
        PROF_T(7);
      }
    } else {
      const float c = 0.08838834764831845f * 1.4426950408889634f;
#pragma unroll 1
      for (int s = 0; s < 64; s++) {
        asm volatile("" : "+r"(t128));
        lane = t128 & 31;
        if (t128 == 0) {
          if (s < 63) mbar_expect_tx(bars + 8 * B_SM, 2560);
          mbar_expect_tx(bars + 8 * B_SX, 8192);
        }
        __syncwarp();
        mem_check(sb, t128, gph, (const uint8_t*)&g_memx[(s - 1) & 3][head % CH_REP][0] + 6144, -1);
        if (s < 63) {
          const uint32_t vb = sb + OFF_QKV + w * 2560 + (lane & 7) * 16;
          uint32_t vm[4], vx[4][4];
          ldmatrix_x4(vb + (lane >> 3) * 640, vm[0], vm[1], vm[2], vm[3]);
#pragma unroll
          for (int j = 0; j < 4; j++)
            ldmatrix_x4(vb + ((j >> 1) * 2 + ((lane >> 3) & 1)) * 640 + (1 + (j & 1) * 2 + (lane >> 4)) * 128, vx[j][0], vx[j][1], vx[j][2], vx[j][3]);
          mbar_wait(bars + 8 * B_SM, s & 1);
          PROF_T(3);
          float sc[5][2];
#pragma unroll
          for (int j = 0; j < 2; j++) {
            const float4 a = lds128f(sb + sl_off(0, j) + lane * 16), b = lds128f(sb + sl_off(1, j) + lane * 16);
            sc[2 * j][0] = a.x + b.x; sc[2 * j][1] = a.y + b.y; sc[2 * j + 1][0] = a.z + b.z; sc[2 * j + 1][1] = a.w + b.w;
          }
          {
            const float2 a = lds64f(sb + sl_off(0, 2) + lane * 8), b = lds64f(sb + sl_off(1, 2) + lane * 8);
            sc[4][0] = a.x + b.x; sc[4][1] = a.y + b.y;
          }
          float m = fmaxf(fmaxf(fmaxf(sc[0][0], sc[0][1]), fmaxf(sc[1][0], sc[1][1])), fmaxf(fmaxf(sc[2][0], sc[2][1]), fmaxf(sc[3][0], sc[3][1])));
          m = fmaxf(m, fmaxf(sc[4][0], sc[4][1]));
          m = fmaxf(m, __shfl_xor_sync(~0u, m, 1));
          m = fmaxf(m, __shfl_xor_sync(~0u, m, 2));
          const float bb = -m * c;
          uint32_t p[5];
#pragma unroll
          for (int j = 0; j < 5; j++) p[j] = pack_bf16(ex2(fmaf(sc[j][0], c, bb)), ex2(fmaf(sc[j][1], c, bb)));
          float oa[4] = {0.f, 0.f, 0.f, 0.f}, ob[4] = {0.f, 0.f, 0.f, 0.f}, ls[4] = {0.f, 0.f, 0.f, 0.f};
          const uint32_t one = 0x3F803F80u;
          mma1688(ls, one, one, p[0]);
          mma1688(oa, vm[0], vm[1], p[0]);
          mma1688(ob, vm[2], vm[3], p[0]);
          mma16816(ls, one, one, one, one, p[1], p[2]);
          mma16816(oa, vx[0][0], vx[0][1], vx[0][2], vx[0][3], p[1], p[2]);
          mma16816(ob, vx[2][0], vx[2][1], vx[2][2], vx[2][3], p[1], p[2]);
          mma16816(ls, one, one, one, one, p[3], p[4]);
          mma16816(oa, vx[1][0], vx[1][1], vx[1][2], vx[1][3], p[3], p[4]);
          mma16816(ob, vx[3][0], vx[3][1], vx[3][2], vx[3][3], p[3], p[4]);
          const float i0 = rcp_fast(ls[0]), i1 = rcp_fast(ls[1]);
          const uint32_t o0 = movmatrix_t(pack_bf16(oa[0] * i0, oa[1] * i1)), o1 = movmatrix_t(pack_bf16(oa[2] * i0, oa[3] * i1));
          const uint32_t o2 = movmatrix_t(pack_bf16(ob[0] * i0, ob[1] * i1)), o3 = movmatrix_t(pack_bf16(ob[2] * i0, ob[3] * i1));
#pragma unroll
          for (int d = 0; d < 2; d++) {
            const uint32_t rsb = mapa(sb, d);
            st_async4(rsb + OFF_OB + w * 512 + lane * 16, o0, o1, o2, o3, rsb + OFF_BAR + 8 * B_O);
          }
          sts128(sb + OFF_OB + w * 512 + lane * 16, make_uint4(o0, o1, o2, o3));
          __syncwarp();
          mbar_arrive_elect(bars + 8 * B_O);
          named_arrive(6, 384);
          PROF_T(4);
#pragma unroll 1
          for (int blk = w;; blk += 3) {
            chain_wo_first(sb, s, wo_addr(sb, blk, lane), lane, blk < 4, pdst + (s & 1) * 65536 + blk * 6144 + (lane ^ psw));
            if (blk == 0 || blk > 2) break;
          }
          named_arrive(3, 384);
          PROF_T(6);
        }
        mbar_wait(bars + 8 * B_SX, s & 1);
        chain_xsoftmax(sb, w, lane);
        named_arrive(4, 384);
        PROF_T(7);
      }
    }
    cluster_sync_all();
  } else {
    asm volatile("setmaxnreg.dec.sync.aligned.u32 24;");
    CH_IDS;
    if (warp == 12) {
      const CUtensorMap* tm = rank == 2 ? &tmWv : (lane & 1) ? &tmWk : &tmWq;
      const int g = lane & 1, col = head * 128 + (rank == 2 ? g * 64 : rank * 64), i = lane >> 1;
      const int nblk = rank == 2 ? 10 : 11;
      asm volatile("barrier.cluster.arrive.aligned;" ::: "memory");
      if (lane == 0) {
        mbar_expect_tx(bars + 8 * B_P0, 22 * 4096); mbar_expect_tx(bars + 8 * B_P1, 20 * 4096);
        mbar_expect_tx(bars + 8 * B_P2, 22 * 4096); mbar_expect_tx(bars + 8 * B_P3, nblk * 8192);
      }
      __syncwarp();
      if (i < 11) tma_load_2d(sb + OFF_WO + g * 45056 + i * 4096, tm, col, (11 + i) * 32, bars + 8 * B_P0);
      __syncwarp();
      if (i < 11) tma_load_2d(sb + OFF_WS + g * WS_SZ + i * 4096, tm, col, i * 32, bars + 8 * B_P2);
      __syncwarp();
      asm volatile("barrier.cluster.wait.aligned;" ::: "memory");
      named_sync(11, 288);
      if (i < 10) tma_load_2d(sb + OFF_WO + g * 45056 + i * 4096, tm, col, (22 + i) * 32, bars + 8 * B_P1);
      __syncwarp();
      named_sync(12, 288);
      if (lane < nblk) tma_load_2d(sb + OFF_WO + lane * 8192, &tmWo, (3 * lane + rank) * 32, head * 128, bars + 8 * B_P3);
    } else {
      if (warp == 13 && head == 0) tma_prefetch_2d(&tmX, (lane & 15) * 64, (rank * 2 + (lane >> 4)) * 32);
      __syncwarp();
      cluster_sync_all();
    }
    __syncwarp();
    if (warp == 14) {
#pragma unroll 1
      for (int s = 0; s < 64; s++) {
        named_sync(1, 288);
        uint32_t g0, c0;
        asm volatile("{.reg .u32 z; .reg .u64 c; ld.volatile.shared.u32 z, [%2]; mov.u32 %0, %%globaltimer_lo; mov.u64 c, %%clock64; cvt.u32.u64 %1, c;}"
                     : "=r"(g0), "=r"(c0) : "r"(bars + 8 * B_BASE) : "memory");
        g0 = (g0 & ~31u) | (s & 31);
        if (lane == 0) st_pub1(&g_ts[s & 3][blockIdx.x * 8], rank == 2 ? g0 - CH_VS : g0);
        if (s > 0) {
          if (rank < 2) named_sync(8, 192);
          if (CH_G1) __nanosleep(CH_G1);
          if (lane == 0) {
            mbar_expect_tx(bars + 8 * B_G, 10240);
            bulk_g2s(sb + OFF_MEM, (const uint8_t*)&g_memx[(s - 1) & 3][head % CH_REP][0] + 6144, 10240, bars + 8 * B_G);
          }
        }
        if (s == 63) break;
        __nanosleep(700);
        int lead = 0;
        for (int n = 0; n < 64; n++) {
          const uint32_t* ts = &g_ts[s & 3][lane * 8];
          const uint32_t a = ld_poll1(ts), b = ld_poll1(ts + 256), c = ld_poll1(ts + 512);
          if (!__any_sync(~0u, (((a ^ g0) | (b ^ g0) | (c ^ g0)) & 31) != 0)) {
            lead = __reduce_max_sync(~0u, max(max((int)(a - g0), (int)(b - g0)), (int)(c - g0)));
            break;
          }
          __nanosleep(200);
        }
        lead = min(lead, 4000);
        if (lane == 0) { sts32(bars + 8 * B_BASE, c0 + ((lead * 29) >> 4)); mbar_arrive(bars + 8 * B_T); }
        PROF_V(18, lead);
        __syncwarp();
      }
    } else if (warp == 12) {
      if (rank < 2) {
        const int red = head * 2 + rank;
        named_sync(4, 416);
#pragma unroll 1
        for (int s = 0; s < 63; s++) {
          named_sync(8, 192);
          uint4* pz = &g_part[s & 1][red][0][0] + lane;
          if (s < 62) named_sync(4, 416);
#pragma unroll 4
          for (int i = 0; i < 16; i++) st_pub4(pz + i * 32, make_uint4(0, 0, 0, 0));
          if (s > 0) st_pub4(&g_memx[(s - 1) & 3][lane >> 4][red * 16 + (lane & 15)], make_uint4(0, 0, 0, 0));
          asm volatile("st.release.gpu.global.u32 [%0], %1;" ::"l"(pz), "r"(0) : "memory");
        }
      } else {
#pragma unroll 1
        for (int s = 0; s <= 64; s++) {
          if (s > 0) {
            named_sync(13, 288);
            if (lane == 0) {
              tma_store_2d(&tmOB, sb + OFF_XL, head * 128, (s - 1) * 32);
              tma_store_2d(&tmOB, sb + OFF_XL + 4096, head * 128 + 64, (s - 1) * 32);
              bulk_commit();
              asm volatile("cp.async.bulk.wait_group.read 0;" ::: "memory");
            }
            __syncwarp();
          }
          if (s < 64) {
            named_sync(7, 288);
            mbar_arrive_remote(bars + 8 * B_LF, lane & 1, lane >> 1);
          }
          if (s > 0 && lane == 0) {
            bulk_wait0();
            asm volatile("fence.proxy.async.global;" ::: "memory");
            asm volatile("red.release.gpu.global.add.u32 [%0], 1;" ::"l"(&g_prog[(s - 1) >> 2]) : "memory");
          }
          __syncwarp();
        }
      }
    } else if (warp == 13) {
      uint32_t ph = 1;
#pragma unroll 1
      for (int cp = rank; cp < 515; cp += 3) {
        mbar_wait(bars + 8 * B_XE + 8 * rank, ph);
        ph ^= 1;
        if (head == (cp & 31) && lane >= 2 && lane < 4 && cp < 464) tma_prefetch_2d(&tmX, (cp & 7) * 128 + (lane & 1) * 64, ((cp >> 3) + 6) * 32);
        if (lane < 3) mbar_expect_remote(mapa(bars + 8 * B_XF + 8 * rank, lane), 8192);
        if (lane < 2) tma_load_2d_mc(sb + OFF_XR + rank * 10240 + lane * 5120, &tmX, (cp & 7) * 128 + lane * 64, min(cp >> 3, 63) * 32, bars + 8 * B_XF + 8 * rank, 7);
      }
    }
    __syncwarp();
    cluster_sync_all();
  }
}

__device__ bf16 g_qkvA[2048 * 3072];
__device__ bf16 g_oA[2048 * 1024];
__device__ bf16 g_oB[2048 * 4096];

typedef CUresult (*EncodeFn)(CUtensorMap*, CUtensorMapDataType, cuuint32_t, void*, const cuuint64_t*, const cuuint64_t*,
                             const cuuint32_t*, const cuuint32_t*, CUtensorMapInterleave, CUtensorMapSwizzle,
                             CUtensorMapL2promotion, CUtensorMapFloatOOBfill);

static void make_map(EncodeFn fn, CUtensorMap* tm, const void* ptr, int rows, int cols, int box_rows, int box_cols, CUtensorMapSwizzle swz) {
  cuuint64_t dims[2] = {(cuuint64_t)cols, (cuuint64_t)rows};
  cuuint64_t strides[1] = {(cuuint64_t)cols * 2};
  cuuint32_t box[2] = {(cuuint32_t)box_cols, (cuuint32_t)box_rows};
  cuuint32_t es[2] = {1, 1};
  fn(tm, CU_TENSOR_MAP_DATA_TYPE_BFLOAT16, 2, (void*)ptr, dims, strides, box, es, CU_TENSOR_MAP_INTERLEAVE_NONE, swz,
     CU_TENSOR_MAP_L2_PROMOTION_L2_256B, CU_TENSOR_MAP_FLOAT_OOB_FILL_NONE);
}

extern "C" void kernel_launch(void* const* d_in, const int* in_sizes, int n_in, void* d_out, int out_size) {
  const bf16* A_x = (const bf16*)d_in[0];
  const bf16* A_wqkv = (const bf16*)d_in[1];
  const bf16* A_wo = (const bf16*)d_in[2];
  const bf16* B_x = (const bf16*)d_in[3];
  const bf16* B_mem0 = (const bf16*)d_in[4];
  const bf16* B_Wq = (const bf16*)d_in[5];
  const bf16* B_Wk = (const bf16*)d_in[6];
  const bf16* B_Wv = (const bf16*)d_in[7];
  const bf16* B_Wo = (const bf16*)d_in[8];
  bf16* out = (bf16*)d_out;

  void* fnp = nullptr;
  cudaDriverEntryPointQueryResult qres;
  cudaGetDriverEntryPoint("cuTensorMapEncodeTiled", &fnp, cudaEnableDefault, &qres);
  EncodeFn enc = (EncodeFn)fnp;
  void *p_qkvA, *p_oA, *p_oB;
  cudaGetSymbolAddress(&p_qkvA, g_qkvA);
  cudaGetSymbolAddress(&p_oA, g_oA);
  cudaGetSymbolAddress(&p_oB, g_oB);

  CUtensorMap mAx, mWqkv, mQkvC, mQ, mKV, mOA, mWoA, mOut;
  make_map(enc, &mAx, A_x, 2048, 1024, 128, 64, CU_TENSOR_MAP_SWIZZLE_128B);
  make_map(enc, &mWqkv, A_wqkv, 1024, 3072, 64, 64, CU_TENSOR_MAP_SWIZZLE_128B);
  make_map(enc, &mQkvC, p_qkvA, 2048, 3072, 64, 64, CU_TENSOR_MAP_SWIZZLE_128B);
  make_map(enc, &mQ, p_qkvA, 2048, 3072, 64, 32, CU_TENSOR_MAP_SWIZZLE_64B);
  make_map(enc, &mKV, p_qkvA, 2048, 3072, 128, 32, CU_TENSOR_MAP_SWIZZLE_64B);
  make_map(enc, &mOA, p_oA, 2048, 1024, 128, 64, CU_TENSOR_MAP_SWIZZLE_128B);
  make_map(enc, &mWoA, A_wo, 1024, 1024, 64, 64, CU_TENSOR_MAP_SWIZZLE_128B);
  make_map(enc, &mOut, out, 2048, 2048, 64, 64, CU_TENSOR_MAP_SWIZZLE_128B);

  CUtensorMap mWq, mWk, mWv, mWoC, mBx, mOB, mWoB, mOBs;
  make_map(enc, &mOBs, p_oB, 2048, 4096, 32, 64, CU_TENSOR_MAP_SWIZZLE_128B);
  make_map(enc, &mWq, B_Wq, 1024, 4096, 32, 64, CU_TENSOR_MAP_SWIZZLE_128B);
  make_map(enc, &mWk, B_Wk, 1024, 4096, 32, 64, CU_TENSOR_MAP_SWIZZLE_128B);
  make_map(enc, &mWv, B_Wv, 1024, 4096, 32, 64, CU_TENSOR_MAP_SWIZZLE_128B);
  make_map(enc, &mWoC, B_Wo, 4096, 1024, 128, 32, CU_TENSOR_MAP_SWIZZLE_64B);
  make_map(enc, &mBx, B_x, 2048, 1024, 32, 64, CU_TENSOR_MAP_SWIZZLE_128B);
  make_map(enc, &mOB, p_oB, 2048, 4096, 128, 64, CU_TENSOR_MAP_SWIZZLE_128B);
  make_map(enc, &mWoB, B_Wo, 4096, 1024, 64, 64, CU_TENSOR_MAP_SWIZZLE_128B);
  void* p_memx;
  cudaGetSymbolAddress(&p_memx, g_memx);
  cudaFuncSetAttribute(chain_kernel, cudaFuncAttributeMaxDynamicSharedMemorySize, CH_SMEM);

  constexpr int G128_SMEM = 3 * (16384 + 16384) + 1024 + 128;
    cudaFuncSetAttribute(gemm_persist_kernel, cudaFuncAttributeMaxDynamicSharedMemorySize, GP_SMEM);
  constexpr int G128T_SMEM = 6 * (16384 + 16384) + 128;
  cudaFuncSetAttribute(gemm_kernel<128, 6, 1, 1>, cudaFuncAttributeMaxDynamicSharedMemorySize, G128T_SMEM);
  cudaFuncSetAttribute(gemm_kernel<128, 3, 2, 1>, cudaFuncAttributeMaxDynamicSharedMemorySize, G128_SMEM);
  cudaFuncSetAttribute(attnA_kernel<2, 4, 2>, cudaFuncAttributeMaxDynamicSharedMemorySize, AT_SMEM);

  cudaStream_t st = cudaStreamPerThread;
  constexpr int NS = 20;
  static cudaStream_t sx[NS] = {};
  static cudaEvent_t evL[NS + 1] = {}, evD[NS] = {};
  if (!sx[0]) {
    for (int i = 0; i < NS; i++) {
      cudaStreamCreateWithFlags(&sx[i], cudaStreamNonBlocking);
      cudaEventCreateWithFlags(&evD[i], cudaEventDisableTiming);
    }
    for (int i = 0; i <= NS; i++) cudaEventCreateWithFlags(&evL[i], cudaEventDisableTiming);
  }
  cudaLaunchAttribute at[2];
  at[1].id = cudaLaunchAttributeClusterDimension;
  at[1].val.clusterDim.x = 2; at[1].val.clusterDim.y = 1; at[1].val.clusterDim.z = 1;
  at[0].id = cudaLaunchAttributeLaunchCompletionEvent;
  at[0].val.launchCompletionEvent.flags = 0;
  cudaLaunchConfig_t cfg = {};
  cfg.attrs = at; cfg.numAttrs = 1;
  cfg.gridDim = dim3(96); cfg.blockDim = dim3(512); cfg.dynamicSmemBytes = CH_SMEM; cfg.stream = st;
  at[0].val.launchCompletionEvent.event = evL[0];
  cudaLaunchKernelEx(&cfg, chain_kernel, mWq, mWk, mWv, mWoC, mBx, mOBs, B_mem0);
  int nk = 0;
  auto next = [&](int dep, int dep2 = -1) {
    cudaStreamWaitEvent(sx[nk], evL[nk], 0);
    if (dep >= 0) cudaStreamWaitEvent(sx[nk], evD[dep], 0);
    if (dep2 >= 0) cudaStreamWaitEvent(sx[nk], evD[dep2], 0);
    cfg.stream = sx[nk];
    at[0].val.launchCompletionEvent.event = evL[nk + 1];
  };
  auto done = [&]() { cudaEventRecord(evD[nk], sx[nk]); return nk++; };
  auto gemm = [&](const CUtensorMap& a, const CUtensorMap& b, const CUtensorMap& c, int K, int tn, int coff, int tm0, int tm1, int gated, int dep, int dep2) {
    next(dep, dep2);
    cfg.gridDim = dim3((tm1 - tm0) * tn); cfg.blockDim = dim3(288); cfg.dynamicSmemBytes = G128_SMEM;
    cudaLaunchKernelEx(&cfg, gemm_kernel<128, 3, 2, 1>, a, b, c, K, tn, coff, tm0, gated, 10 + nk);
    return done();
  };
  auto attn = [&](int tm0, int tm1, int h0, int nh, int dep) {
    next(dep);
    cfg.gridDim = dim3((tm1 - tm0) * nh); cfg.blockDim = dim3(256); cfg.dynamicSmemBytes = AT_SMEM;
    cudaLaunchKernelEx(&cfg, attnA_kernel<2, 4, 2>, mQ, mKV, (bf16*)p_oA, tm0, h0, nh, 10 + nk);
    return done();
  };
#define SCHED a5b4aBo0aGo0o0
#define STR2(x) #x
#define STR(x) STR2(x)
  next(-1);
  cfg.gridDim = dim3(36); cfg.blockDim = dim3(288); cfg.dynamicSmemBytes = GP_SMEM;
  cudaLaunchKernelEx(&cfg, gemm_persist_kernel, mAx, mWqkv, mQkvC, 1024, 9, 144, 10);
  const int q1 = done();
  const int q2 = gemm(mAx, mWqkv, mQkvC, 1024, 6, 0, 0, 16, 2, -1, -1);
  int ra = 0, rb = 0, na = 0, no = 0, ak[8], ar[9] = {0}, a0 = -1;
  for (const char* e = STR(SCHED); *e; e += 2) {
    const int n = e[1] <= '9' ? e[1] - '0' : e[1] - 'A' + 10;
    if (e[0] == 'a') {
      if (na == 0) { a0 = attn(0, n, 0, 24, q1); ak[0] = attn(0, n, 24, 8, q2); }
      else ak[na] = attn(ra, n, 0, 32, -1);
      ra = n; ar[++na] = ra;
    } else if (e[0] == 'b') {
      gemm(mOB, mWoB, mOut, 4096, 8, 1024, rb, n, 1, -1, -1);
      rb = n;
    } else if (e[0] == 'p') {
      next(ak[no], no == 0 ? a0 : -1);
      cfg.gridDim = dim3((ar[no + 1] - ar[no]) * 8); cfg.blockDim = dim3(288); cfg.dynamicSmemBytes = G128T_SMEM;
      cudaLaunchKernelEx(&cfg, gemm_kernel<128, 6, 1, 1>, mOA, mWoA, mOut, 1024, 8, 0, ar[no], 0, 10 + nk);
      done();
      no++;
    } else {
      gemm(mOA, mWoA, mOut, 1024, 8, 0, ar[no], ar[no + 1], 0, ak[no], no == 0 ? a0 : -1);
      no++;
    }
  }
  {
    cudaStreamWaitEvent(sx[nk], evD[q2], 0);
#define GATE_CNT 64
    gate_kernel<<<1, 32, 0, sx[nk]>>>(15, GATE_CNT);
    int lo = 0, hi = 0;
    cudaDeviceGetStreamPriorityRange(&lo, &hi);
    at[0].id = cudaLaunchAttributePriority;
    at[0].val.priority = hi;
    cfg.stream = sx[nk];
    cfg.gridDim = dim3((16 - rb) * 8); cfg.blockDim = dim3(288); cfg.dynamicSmemBytes = G128T_SMEM;
    cudaLaunchKernelEx(&cfg, gemm_kernel<128, 6, 1, 1>, mOB, mWoB, mOut, 4096, 8, 1024, rb, 1, 5);
    done();
  }
  cudaMemsetAsync(p_memx, 0, sizeof(g_memx), st);
  for (int i = 0; i < nk; i++) cudaStreamWaitEvent(st, evD[i], 0);
}
```
